```python
import torch

def _softmax(x, axis=-1):
    return torch.softmax(x, dim=axis)
def _gelu(x):
    return torch.nn.functional.gelu(x, approximate="tanh")
def _silu(x):
    return torch.nn.functional.silu(x)
def _sigmoid(x):
    return torch.sigmoid(x)
def _layernorm(x, axis=-1, eps=1e-5):
    m = x.mean(dim=axis, keepdim=True)
    v = x.var(dim=axis, keepdim=True, unbiased=False)
    return (x - m) / torch.sqrt(v + eps)
def _scatter_add(tgt, idx, src, axis=0):
    return tgt.clone().index_add_(axis, idx, src)
def _segment_sum(src, seg, n):
    out = torch.zeros((n,) + src.shape[1:], dtype=src.dtype)
    return out.index_add_(0, seg, src)
def _pad(x, pw):
    flat = tuple(v for pair in reversed(pw) for v in pair)
    return torch.nn.functional.pad(x, flat)

kernel_name = 'gated_mix__ssm_conv_s4__mixer_channel_mlp__prompt'

def setup_inputs():

    _w = (lambda a: (lambda t: t.to(torch.bfloat16) if t.is_floating_point() else t)(torch.as_tensor(a)))
    def _A_setup():
        B, L, D, N = 1, 2048, 576, 128
        A_re = -(lambda _x: torch.exp(torch.as_tensor(_x)))((lambda *s: torch.randn(*s, dtype=torch.bfloat16) * 3.2)(D, N))
        A_im = torch.pi * (lambda *s: torch.randn(*s, dtype=torch.bfloat16) * 0.1)(D, N)
        B_re = (lambda *s: torch.randn(*s, dtype=torch.bfloat16) * 0.2)(D, N)
        B_im = (lambda *s: torch.randn(*s, dtype=torch.bfloat16) * 0.2)(D, N)
        C_re = (lambda *s: torch.randn(*s, dtype=torch.bfloat16) * 0.2)(D, N)
        C_im = (lambda *s: torch.randn(*s, dtype=torch.bfloat16) * 0.2)(D, N)
        log_dt = (lambda *s: torch.randn(*s, dtype=torch.bfloat16) * 0.1)(D) * 0.5 - 4.0
        Dskip = (lambda *s: torch.randn(*s, dtype=torch.bfloat16) * 0.1)(D)
        return {
            "u": _w((lambda *s: torch.randn(*s, dtype=torch.bfloat16) * 0.05)(B, L, D)),
            "A_re": _w(A_re),
            "A_im": _w(A_im),
            "B_re": _w(B_re),
            "B_im": _w(B_im),
            "C_re": _w(C_re),
            "C_im": _w(C_im),
            "log_dt": _w(log_dt),
            "Dskip": _w(Dskip),
        }
    _A_in = _A_setup()

    def _B_setup():
        B, S, D, F = 1, 2048, 576, 4608
        return {
            "x": _w((lambda *s: torch.randn(*s, dtype=torch.bfloat16) * 0.05)(B, S, D)),
            "w1": _w((lambda *s: torch.randn(*s, dtype=torch.bfloat16) * 0.8)(D, F) * (D ** -0.5)),
            "b1": _w((lambda *s: torch.randn(*s, dtype=torch.bfloat16) * 0.4)(F)),
            "w2": _w((lambda *s: torch.randn(*s, dtype=torch.bfloat16) * 0.05)(F, D) * (F ** -0.5)),
            "b2": _w((lambda *s: torch.randn(*s, dtype=torch.bfloat16) * 0.05)(D)),
        }
    _B_in = _B_setup()

    return {
        "A_u": _A_in["u"],
        "A_A_re": _A_in["A_re"],
        "A_A_im": _A_in["A_im"],
        "A_B_re": _A_in["B_re"],
        "A_B_im": _A_in["B_im"],
        "A_C_re": _A_in["C_re"],
        "A_C_im": _A_in["C_im"],
        "A_log_dt": _A_in["log_dt"],
        "A_Dskip": _A_in["Dskip"],
        "B_x": _B_in["x"],
        "B_w1": _B_in["w1"],
        "B_b1": _B_in["b1"],
        "B_w2": _B_in["w2"],
        "B_b2": _B_in["b2"],
        "gate_w": _w((lambda *s: torch.randn(*s, dtype=torch.bfloat16) * 0.05)(576) * 16.0),
    }

def reference(A_u, A_A_re, A_A_im, A_B_re, A_B_im, A_C_re, A_C_im, A_log_dt, A_Dskip, B_x, B_w1, B_b1, B_w2, B_b2, gate_w):
    def _A_ref(u, A_re, A_im, B_re, B_im, C_re, C_im, log_dt, Dskip):
        Bsz, L, D = u.shape
        dt = torch.exp(log_dt)[:, None]
        A = A_re + 1j * A_im
        Bc = B_re + 1j * B_im
        Cc = C_re + 1j * C_im
        logdA = dt * A
        dB = dt * Bc
        l = (lambda x, dt: x.to(dt))(torch.arange(L), A_re.dtype)
        P = torch.exp(logdA[:, :, None] * l[None, None, :])
        K = torch.einsum("dn,dnl,dn->dl", Cc, P, dB).real
        L2 = 2 * L
        Kp = _pad(K, ((0, 0), (0, L)))
        up = (lambda x, *d: x.permute(*d))(u, 0, 2, 1)
        up = _pad(up, ((0, 0), (0, 0), (0, L)))
        Kf = (lambda x, axes=(-2,-1): torch.fft.rfft2(x.float(), dim=axes))(Kp[:, None, :], axes=(-2, -1))
        Uf = (lambda x, axes=(-2,-1): torch.fft.rfft2(x.float(), dim=axes))(up[:, :, None, :], axes=(-2, -1))
        Yf = Uf * Kf[None, :, :, :]
        y = (lambda x, s, axes=(-2,-1): torch.fft.irfft2(x, s=s, dim=axes).to(torch.bfloat16))(Yf, (1, L2), axes=(-2, -1))[:, :, 0, :L]
        y = (lambda x, *d: x.permute(*d))(y, 0, 2, 1) + u * Dskip[None, None, :]
        return y

    def _B_ref(x, w1, b1, w2, b2):
        y = _layernorm(x, axis=-1)
        h = _gelu(torch.einsum("bsd,df->bsf", y, w1) + b1)
        return torch.einsum("bsf,fd->bsd", h, w2) + b2

    x = A_u
    g = _sigmoid((x * gate_w).sum(-1, keepdims=True))
    a = _A_ref(x, A_A_re, A_A_im, A_B_re, A_B_im, A_C_re, A_C_im, A_log_dt, A_Dskip)
    b = _B_ref(x, B_w1, B_b1, B_w2, B_b2)
    return g * a + (1 - g) * b
```

```cpp
#include <cuda_runtime.h>
#include <cuda_bf16.h>
#include <cuda.h>
#include <stdint.h>

#define PREGS "24"
#define CREGS "240"
#define L_SEQ 2048
#define D_MOD 576
#define F_HID 4608
#define N_ST 128

__device__ __align__(1024) __nv_bfloat16 g_aT[D_MOD * L_SEQ];
__device__ __align__(1024) uint32_t g_slots[16 * 8 * 3 * 4096];
__device__ __align__(1024) uint32_t g_slots8[16 * 8 * 4096];
__device__ __align__(1024) __nv_bfloat16 g_xn[L_SEQ * D_MOD];
__device__ __align__(1024) __nv_bfloat16 g_uT[D_MOD * L_SEQ];
__device__ uint2 g_gate[L_SEQ];
__device__ unsigned int g_lnflag[33];
__device__ unsigned int g_flags[16 * 16];
struct Scratch {
  __nv_bfloat16* aT; __nv_bfloat16* xn; __nv_bfloat16* uT; uint2* gate; uint32_t* slots; uint32_t* slots8; unsigned int* flags; unsigned int* lnflag;
  long long* dbg;
};
#define DBG_T(i)
#define DBG_X(i)
#define DBG_Y(i)
#define DBG_H(i)
#define DBG_G(i)

__device__ __forceinline__ uint32_t smem_u32(const void* p) { return (uint32_t)__cvta_generic_to_shared(p); }
__device__ __forceinline__ void mbar_init(uint32_t bar, int cnt) {
  asm volatile("mbarrier.init.shared::cta.b64 [%0], %1;" ::"r"(bar), "r"(cnt));
}
__device__ __forceinline__ void mbar_expect_tx(uint32_t bar, uint32_t bytes) {
  asm volatile("mbarrier.arrive.expect_tx.shared::cta.b64 _, [%0], %1;" ::"r"(bar), "r"(bytes) : "memory");
}
__device__ __forceinline__ void mbar_arrive(uint32_t bar) {
  asm volatile("mbarrier.arrive.shared::cta.b64 _, [%0];" ::"r"(bar) : "memory");
}
__device__ __forceinline__ void mbar_arrive_remote(uint32_t remote_bar) {
  asm volatile("mbarrier.arrive.relaxed.cluster.shared::cluster.b64 _, [%0];" ::"r"(remote_bar) : "memory");
}
__device__ __forceinline__ bool mbar_try(uint32_t bar, uint32_t parity) {
  uint32_t ok;
  asm volatile("{\n.reg .pred p;\nmbarrier.try_wait.parity.shared::cta.b64 p, [%1], %2;\nselp.u32 %0,1,0,p;\n}"
               : "=r"(ok) : "r"(bar), "r"(parity) : "memory");
  return ok;
}
__device__ __forceinline__ bool mbar_try_cluster(uint32_t bar, uint32_t parity) {
  uint32_t ok;
  asm volatile("{\n.reg .pred p;\nmbarrier.try_wait.parity.acquire.cluster.shared::cta.b64 p, [%1], %2;\nselp.u32 %0,1,0,p;\n}"
               : "=r"(ok) : "r"(bar), "r"(parity) : "memory");
  return ok;
}
__device__ __forceinline__ void mbar_wait(uint32_t bar, uint32_t parity) {
  asm volatile(
      "{\n.reg .pred p;\n.reg .u32 n;\nmov.u32 n, 0;\n"
      "W_%=:\nmbarrier.try_wait.parity.shared::cta.b64 p, [%0], %1;\n@p bra D_%=;\n"
      "add.u32 n, n, 1;\nsetp.lt.u32 p, n, 400000;\n@p bra W_%=;\ntrap;\nD_%=:\n}"
      ::"r"(bar), "r"(parity) : "memory");
}
__device__ __forceinline__ void tma2d(uint32_t dst, const CUtensorMap* tm, int c0, int c1, uint32_t bar) {
  asm volatile("cp.async.bulk.tensor.2d.shared::cluster.global.mbarrier::complete_tx::bytes [%0], [%1, {%3, %4}], [%2];"
               ::"r"(dst), "l"(tm), "r"(bar), "r"(c0), "r"(c1) : "memory");
}
__device__ __forceinline__ void wait_flag(unsigned int* flag, unsigned int target) {
  asm volatile(
      "{\n.reg .pred p;\n.reg .u32 n, v;\nmov.u32 n, 0;\n"
      "W_%=:\nld.acquire.gpu.global.u32 v, [%0];\nsetp.ge.u32 p, v, %1;\n@p bra D_%=;\n"
      "nanosleep.u32 32;\nadd.u32 n, n, 1;\nsetp.lt.u32 p, n, 4000000;\n@p bra W_%=;\ntrap;\nD_%=:\n}"
      ::"l"(flag), "r"(target) : "memory");
}
__device__ __forceinline__ void bulk_g2s(uint32_t dst, const void* src, uint32_t bytes, uint32_t bar) {
  asm volatile("cp.async.bulk.shared::cluster.global.mbarrier::complete_tx::bytes [%0], [%1], %2, [%3];"
               ::"r"(dst), "l"(src), "r"(bytes), "r"(bar) : "memory");
}
__device__ __forceinline__ uint32_t mapa(uint32_t addr, uint32_t rank) {
  uint32_t r;
  asm("mapa.shared::cluster.u32 %0, %1, %2;" : "=r"(r) : "r"(addr), "r"(rank));
  return r;
}
__device__ __forceinline__ void st_async_v4(uint32_t raddr, float a, float b, float c, float d, uint32_t rbar) {
  asm volatile("st.async.weak.shared::cluster.mbarrier::complete_tx::bytes.v4.f32 [%0], {%1,%2,%3,%4}, [%5];"
               ::"r"(raddr), "f"(a), "f"(b), "f"(c), "f"(d), "r"(rbar) : "memory");
}
__device__ __forceinline__ float4 lds128f(uint32_t addr) {
  float4 v;
  asm volatile("ld.shared.v4.f32 {%0,%1,%2,%3}, [%4];" : "=f"(v.x), "=f"(v.y), "=f"(v.z), "=f"(v.w) : "r"(addr));
  return v;
}
__device__ __forceinline__ uint32_t lds32(uint32_t addr) {
  uint32_t v;
  asm volatile("ld.shared.u32 %0, [%1];" : "=r"(v) : "r"(addr));
  return v;
}
__device__ __forceinline__ void sts128(uint32_t addr, uint32_t a, uint32_t b, uint32_t c, uint32_t d) {
  asm volatile("st.shared.v4.u32 [%0], {%1,%2,%3,%4};" ::"r"(addr), "r"(a), "r"(b), "r"(c), "r"(d) : "memory");
}
__device__ __forceinline__ void sts128f(uint32_t addr, float a, float b, float c, float d) {
  asm volatile("st.shared.v4.f32 [%0], {%1,%2,%3,%4};" ::"r"(addr), "f"(a), "f"(b), "f"(c), "f"(d) : "memory");
}
__device__ __forceinline__ uint64_t make_desc(uint32_t addr, uint32_t lbo, uint32_t sbo, uint32_t swz) {
  return (uint64_t)((addr & 0x3FFFF) >> 4) | ((uint64_t)((lbo & 0x3FFFF) >> 4) << 16) |
         ((uint64_t)((sbo & 0x3FFFF) >> 4) << 32) | ((uint64_t)swz << 62);
}
#define WG_FENCE() asm volatile("wgmma.fence.sync.aligned;" ::: "memory")
#define WG_COMMIT() asm volatile("wgmma.commit_group.sync.aligned;" ::: "memory")
template <int n> __device__ __forceinline__ void wg_wait() {
  asm volatile("wgmma.wait_group.sync.aligned %0;" ::"n"(n) : "memory");
}
__device__ __forceinline__ uint32_t pack_bf16(float lo, float hi) {
  uint32_t r;
  asm("cvt.rn.bf16x2.f32 %0, %1, %2;" : "=r"(r) : "f"(hi), "f"(lo));
  return r;
}
__device__ __forceinline__ float bf_lo(uint32_t p) { return __uint_as_float(p << 16); }
__device__ __forceinline__ float bf_hi(uint32_t p) { return __uint_as_float(p & 0xffff0000u); }
__device__ __forceinline__ float bf_round(float x) { return __bfloat162float(__float2bfloat16_rn(x)); }
__device__ __forceinline__ uint32_t bf2_add(uint32_t a, uint32_t b) {
  uint32_t r;
  asm("add.rn.bf16x2 %0, %1, %2;" : "=r"(r) : "r"(a), "r"(b));
  return r;
}
__device__ __forceinline__ uint32_t bf2_mul(uint32_t a, uint32_t b) {
  uint32_t r;
  asm("mul.rn.bf16x2 %0, %1, %2;" : "=r"(r) : "r"(a), "r"(b));
  return r;
}
__device__ __forceinline__ float tanh_fast(float x) {
  float r;
  asm("tanh.approx.f32 %0, %1;" : "=f"(r) : "f"(x));
  return r;
}
__device__ __forceinline__ float gelu_tanh(float v) {
  float p = fmaf(v * v, 0.0356774081363f, 0.7978845608029f);
  float t = tanh_fast(v * p);
  float hv = 0.5f * v;
  return fmaf(hv, t, hv);
}
__device__ __forceinline__ uint32_t gelu_pack(float a0, float a1, uint32_t bias2) {
  uint32_t p = bf2_add(pack_bf16(a0, a1), bias2);
  return pack_bf16(gelu_tanh(bf_lo(p)), gelu_tanh(bf_hi(p)));
}

#define R8(a, o) "+f"(a[o]), "+f"(a[o + 1]), "+f"(a[o + 2]), "+f"(a[o + 3]), "+f"(a[o + 4]), "+f"(a[o + 5]), "+f"(a[o + 6]), "+f"(a[o + 7])
#define W8(a, o) "=f"(a[o]), "=f"(a[o + 1]), "=f"(a[o + 2]), "=f"(a[o + 3]), "=f"(a[o + 4]), "=f"(a[o + 5]), "=f"(a[o + 6]), "=f"(a[o + 7])
#define REGS48 "{%0,%1,%2,%3,%4,%5,%6,%7,%8,%9,%10,%11,%12,%13,%14,%15,%16,%17,%18,%19,%20,%21,%22,%23," \
               "%24,%25,%26,%27,%28,%29,%30,%31,%32,%33,%34,%35,%36,%37,%38,%39,%40,%41,%42,%43,%44,%45,%46,%47}"
#define REGS32 "{%0,%1,%2,%3,%4,%5,%6,%7,%8,%9,%10,%11,%12,%13,%14,%15,%16,%17,%18,%19,%20,%21,%22,%23," \
               "%24,%25,%26,%27,%28,%29,%30,%31}"
#define DESC_HI_A  "0x40000040"
#define DESC_HI_B1 "0x80000020"
#define DESC_HI_B2 "0x40000040"
template <bool ACC, int OA, int OB>
__device__ __forceinline__ void wgmma_ss_n96(float (&d)[48], uint32_t da, uint32_t db) {
  if (ACC)
    asm volatile("{\n.reg .b64 xa, xb;\n.reg .b32 la, lb;\nadd.u32 la, %48, %50;\nadd.u32 lb, %49, %51;\n"
                 "mov.b64 xa, {la, " DESC_HI_A "};\nmov.b64 xb, {lb, " DESC_HI_B1 "};\n"
                 "wgmma.mma_async.sync.aligned.m64n96k16.f32.bf16.bf16 " REGS48 ", xa, xb, 1, 1, 1, 0, 1;\n}\n"
                 : R8(d, 0), R8(d, 8), R8(d, 16), R8(d, 24), R8(d, 32), R8(d, 40) : "r"(da), "r"(db), "n"(OA), "n"(OB));
  else
    asm volatile("{\n.reg .b64 xa, xb;\n.reg .b32 la, lb;\nadd.u32 la, %48, %50;\nadd.u32 lb, %49, %51;\n"
                 "mov.b64 xa, {la, " DESC_HI_A "};\nmov.b64 xb, {lb, " DESC_HI_B1 "};\n"
                 "wgmma.mma_async.sync.aligned.m64n96k16.f32.bf16.bf16 " REGS48 ", xa, xb, 0, 1, 1, 0, 1;\n}\n"
                 : W8(d, 0), W8(d, 8), W8(d, 16), W8(d, 24), W8(d, 32), W8(d, 40) : "r"(da), "r"(db), "n"(OA), "n"(OB));
}
template <bool ACC, int OB>
__device__ __forceinline__ void wgmma_rs_n64(float (&d)[32], uint32_t a0, uint32_t a1, uint32_t a2, uint32_t a3, uint32_t db) {
  if (ACC)
    asm volatile("{\n.reg .b64 xb;\n.reg .b32 lb;\nadd.u32 lb, %36, %37;\nmov.b64 xb, {lb, " DESC_HI_B2 "};\n"
                 "wgmma.mma_async.sync.aligned.m64n64k16.f32.bf16.bf16 " REGS32 ", {%32,%33,%34,%35}, xb, 1, 1, 1, 1;\n}\n"
                 : R8(d, 0), R8(d, 8), R8(d, 16), R8(d, 24) : "r"(a0), "r"(a1), "r"(a2), "r"(a3), "r"(db), "n"(OB));
  else
    asm volatile("{\n.reg .b64 xb;\n.reg .b32 lb;\nadd.u32 lb, %36, %37;\nmov.b64 xb, {lb, " DESC_HI_B2 "};\n"
                 "wgmma.mma_async.sync.aligned.m64n64k16.f32.bf16.bf16 " REGS32 ", {%32,%33,%34,%35}, xb, 0, 1, 1, 1;\n}\n"
                 : W8(d, 0), W8(d, 8), W8(d, 16), W8(d, 24) : "r"(a0), "r"(a1), "r"(a2), "r"(a3), "r"(db), "n"(OB));
}
template <int OA, int OB>
__device__ __forceinline__ void wgmma_ss_n64(float (&d)[32], uint32_t da, uint32_t db) {
  asm volatile("{\n.reg .b64 xa, xb;\n.reg .b32 la, lb;\nadd.u32 la, %32, %34;\nadd.u32 lb, %33, %35;\n"
               "mov.b64 xa, {la, " DESC_HI_A "};\nmov.b64 xb, {lb, " DESC_HI_B2 "};\n"
               "wgmma.mma_async.sync.aligned.m64n64k16.f32.bf16.bf16 " REGS32 ", xa, xb, 1, 1, 1, 0, 1;\n}\n"
               : R8(d, 0), R8(d, 8), R8(d, 16), R8(d, 24) : "r"(da), "r"(db), "n"(OA), "n"(OB));
}
template <int N> __device__ __forceinline__ void fence_regs(float (&d)[N]) {
#pragma unroll
  for (int i = 0; i < N; i++) asm volatile("" : "+f"(d[i])::"memory");
}

__device__ __forceinline__ void ln_load(const __nv_bfloat16* __restrict__ x, const __nv_bfloat16* __restrict__ gate_w,
                                        int row, int lane, uint32_t (&w)[9], uint32_t (&gw)[9]) {
  const uint32_t* xr = reinterpret_cast<const uint32_t*>(x + (size_t)row * D_MOD) + lane;
  const uint32_t* gwp = reinterpret_cast<const uint32_t*>(gate_w) + lane;
#pragma unroll
  for (int j = 0; j < 9; j++) {
    asm volatile("ld.global.nc.u32 %0, [%1];" : "=r"(w[j]) : "l"(xr + j * 32));
    asm volatile("ld.global.nc.u32 %0, [%1];" : "=r"(gw[j]) : "l"(gwp + j * 32));
  }
}
__device__ __forceinline__ void ln_row(int row, int lane, const Scratch& sc, const uint32_t (&w)[9], const uint32_t (&gw)[9],
                                       uint32_t* dst) {
  float s = 0.f, gsum = 0.f;
#pragma unroll
  for (int j = 0; j < 9; j++) {
    uint32_t pr2 = bf2_mul(w[j], gw[j]);
    s += bf_lo(w[j]) + bf_hi(w[j]);
    gsum += bf_lo(pr2) + bf_hi(pr2);
  }
#pragma unroll
  for (int o = 1; o < 32; o <<= 1) { s += __shfl_xor_sync(~0u, s, o); gsum += __shfl_xor_sync(~0u, gsum, o); }
  const float mean = s * (1.0f / 576.0f);
  float vs = 0.f;
#pragma unroll
  for (int j = 0; j < 9; j++) {
    float d0 = bf_lo(w[j]) - mean, d1 = bf_hi(w[j]) - mean;
    vs = fmaf(d0, d0, vs); vs = fmaf(d1, d1, vs);
  }
#pragma unroll
  for (int o = 1; o < 32; o <<= 1) vs += __shfl_xor_sync(~0u, vs, o);
  const float mb = bf_round(mean);
  const float vb = bf_round(vs * (1.0f / 576.0f));
  const float rinv = __frcp_rn(bf_round(__fsqrt_rn(bf_round(vb + 1e-5f))));
  const uint32_t nm2 = pack_bf16(-mb, -mb);
#pragma unroll
  for (int j = 0; j < 9; j++) {
    uint32_t dd = bf2_add(w[j], nm2);
    dst[j * 32 + lane] = pack_bf16(bf_lo(dd) * rinv, bf_hi(dd) * rinv);
  }
  if (lane == 0) {
    float gv = bf_round(__fdividef(1.0f, 1.0f + __expf(-bf_round(gsum))));
    float og = bf_round(1.0f - gv);
    sc.gate[row] = make_uint2(pack_bf16(gv, gv), pack_bf16(og, og));
  }
}

constexpr int SS_UA = 4752, SS_UB = SS_UA + 3616, SS_W3A = SS_UB + 3616, SS_W3B = SS_W3A + 3616, SS_W5 = SS_W3B + 3616,
              SS_W7 = SS_W5 + 3104, SS_W9 = SS_W7 + 2112, SS_TAP = SS_W9 + 2112;
constexpr int TP_0 = 0, TP_W3A = 580, TP_UA = 716, TP_UB = 852, TP_W3B = 988, TP_W5 = 1248, TP_W9 = 1448, TP_W7 = 1648;
constexpr int SS_TAPC = 1856;
constexpr int SS_KB = SS_TAP + 2 * SS_TAPC;
constexpr int SS_Y = SS_KB + 16;
constexpr int SS_YB = 8320;
constexpr int SS_CH = SS_Y + 2 * SS_YB + 5248;
constexpr int SS_CONST = SS_Y, SS_KC = SS_CONST + 10240;
constexpr int SS_XN = 4 * SS_CH;
__device__ __forceinline__ int xg_off(int box) { return box < 4 ? 4864 + box * 4096 : SS_CH + 4928 + (box - 4) * 4096; }
constexpr int SSM_SMEM = SS_XN + 18432 + 16;

__device__ __forceinline__ void mma_bf16(float (&d)[4], uint32_t a0, uint32_t a1, uint32_t a2, uint32_t a3, uint32_t b0, uint32_t b1) {
  asm("mma.sync.aligned.m16n8k16.row.col.f32.bf16.bf16.f32 {%0,%1,%2,%3}, {%4,%5,%6,%7}, {%8,%9}, {%0,%1,%2,%3};"
               : "+f"(d[0]), "+f"(d[1]), "+f"(d[2]), "+f"(d[3]) : "r"(a0), "r"(a1), "r"(a2), "r"(a3), "r"(b0), "r"(b1));
}
__device__ __forceinline__ void mma_tf32(float (&d)[4], float a0, float a1, float a2, float a3, float b0, float b1) {
  asm("mma.sync.aligned.m16n8k8.row.col.f32.tf32.tf32.f32 {%0,%1,%2,%3}, {%4,%5,%6,%7}, {%8,%9}, {%0,%1,%2,%3};"
               : "+f"(d[0]), "+f"(d[1]), "+f"(d[2]), "+f"(d[3])
               : "r"(__float_as_uint(a0)), "r"(__float_as_uint(a1)), "r"(__float_as_uint(a2)), "r"(__float_as_uint(a3)),
                 "r"(__float_as_uint(b0)), "r"(__float_as_uint(b1)));
}
__device__ __forceinline__ float2 cexp_l(float al, float th, float l) {
  float mg;
  asm("ex2.approx.ftz.f32 %0, %1;" : "=f"(mg) : "f"(al * l));
  const float tr = th * l;
  return make_float2(mg * __cosf(tr), mg * __sinf(tr));
}
__device__ __forceinline__ float2 cmul(float2 a, float2 b) {
  return make_float2(fmaf(a.x, b.x, -a.y * b.y), fmaf(a.x, b.y, a.y * b.x));
}
__device__ __forceinline__ float2 csq(float2 a) { return make_float2(fmaf(a.x, a.x, -a.y * a.y), 2.0f * a.x * a.y); }

struct SsmArgs {
  const __nv_bfloat16 *u, *Are, *Aim, *Bre, *Bim, *Cre, *Cim, *logdt, *Dskip, *gate_w;
  const char *w1, *w2;
};
#define SM_U32(p) (*reinterpret_cast<uint32_t*>(p))
#define SM_F32(p) (*reinterpret_cast<float*>(p))
#define SM_U16(p) (*reinterpret_cast<unsigned short*>(p))
#define SM_U2(p) (*reinterpret_cast<uint2*>(p))
#define SM_F2(p) (*reinterpret_cast<float2*>(p))
#define SM_U4(p) (*reinterpret_cast<uint4*>(p))
#define SM_F4(p) (*reinterpret_cast<float4*>(p))

__device__ __forceinline__ void load_tquad(uint32_t (&q)[4], const char* tp, int k) {
  q[0] = *(const volatile uint32_t*)(tp - 32 * k);
  q[1] = *(const volatile uint32_t*)(tp - 32 * k - 16);
  q[2] = *(const volatile uint32_t*)(tp - 32 * k + 16);
  q[3] = *(const volatile uint32_t*)(tp - 32 * k);
}
__device__ __forceinline__ float ldg_bf16(const __nv_bfloat16* p) {
  unsigned short v;
  asm volatile("ld.global.nc.u16 %0, [%1];" : "=h"(v) : "l"(p));
  return __uint_as_float((uint32_t)v << 16);
}
__device__ __forceinline__ void ldsm4(uint32_t (&r)[4], uint32_t addr) {
  asm volatile("ldmatrix.sync.aligned.m8n8.x4.shared.b16 {%0,%1,%2,%3}, [%4];"
               : "=r"(r[0]), "=r"(r[1]), "=r"(r[2]), "=r"(r[3]) : "r"(addr) : "memory");
}
__device__ __forceinline__ void ldsm4t(uint32_t (&r)[4], uint32_t addr) {
  asm volatile("ldmatrix.sync.aligned.m8n8.x4.trans.shared.b16 {%0,%1,%2,%3}, [%4];"
               : "=r"(r[0]), "=r"(r[1]), "=r"(r[2]), "=r"(r[3]) : "r"(addr) : "memory");
}
template <int I0, int I1, int K0, int K1, int JMIN, int RB>
__device__ __forceinline__ void band(float (&acc)[I1 - I0][4], const char* tp, uint32_t sa, uint32_t za, int lane) {
  uint32_t tq[K1 - K0][4];
#pragma unroll
  for (int k = K0; k < K1; k++) load_tquad(tq[k - K0], tp, k);
  constexpr int JL = (I0 - K1 + 1 > JMIN) ? I0 - K1 + 1 : JMIN, JH = I1 - 1 - K0;
  constexpr int JP = (JL >= 0) ? (JL & ~1) : -2;
#pragma unroll
  for (int J2 = JP; J2 <= JH; J2 += 2) {
    uint32_t b[4];
    ldsm4t(b, (J2 < 0 && lane < 31) ? za : sa + J2 * 16 * RB);
#pragma unroll
    for (int hf = 0; hf < 2; hf++) {
      const int J = J2 + hf;
#pragma unroll
      for (int k = K0; k < K1; k++) {
        const int I = J + k;
        if (J >= JL && J <= JH && I >= I0 && I < I1)
          mma_bf16(acc[I - I0], tq[k - K0][0], tq[k - K0][1], tq[k - K0][2], tq[k - K0][3], b[2 * hf], b[2 * hf + 1]);
      }
    }
  }
}
template <int I0, int I1>
__device__ __forceinline__ void p8_tiles(char* cb, const char* tp, int lane) {
  float acc[I1 - I0][4];
#pragma unroll
  for (int i = 0; i < I1 - I0; i++) { acc[i][0] = acc[i][1] = acc[i][2] = acc[i][3] = 0.f; }
  const uint32_t za = smem_u32(cb), sa = za + 32 + lane * 16;
  band<I0, I1, 2, 5, -1, 16>(acc, tp + TP_W3A + 160, sa + SS_W3A, za, lane);
  band<I0, I1, 2, 5, 0, 16>(acc, tp + TP_UA + 160, sa + SS_UA, za, lane);
  band<I0, I1, 2, 5, 0, 16>(acc, tp + TP_UB + 160, sa + SS_UB, za, lane);
  band<I0, I1, 2, 9, 0, 16>(acc, tp + TP_W3B + 288, sa + SS_W3B, za, lane);
  band<I0, I1, 4, 9, -1, 16>(acc, tp + TP_W5 + 288, sa + SS_W5, za, lane);
  char* a = cb + SS_Y + SS_YB + 4 * (8 * (lane >> 2) + 2 * (lane & 3));
#pragma unroll
  for (int I = I0; I < I1; I++) {
    SM_F2(a + 4 * (128 * I + 4 * (I >> 1))) = make_float2(acc[I - I0][0], acc[I - I0][1]);
    SM_F2(a + 4 * (128 * I + 4 * (I >> 1)) + 256) = make_float2(acc[I - I0][2], acc[I - I0][3]);
  }
}
__device__ __forceinline__ float2 cmulc(float2 a, float2 b) {
  return make_float2(fmaf(a.x, b.x, -a.y * b.y), fmaf(-a.x, b.y, -a.y * b.x));
}

__global__ void __cluster_dims__(2, 1, 1) __launch_bounds__(512, 1) ssm_kernel(const __grid_constant__ CUtensorMap tm_x, const SsmArgs ar, const Scratch sc) {
  extern __shared__ __align__(1024) char smem_raw[];
  asm volatile("griddepcontrol.launch_dependents;");
  DBG_G(30);
  const int tid = threadIdx.x, lane = tid & 31;
  const int warp = __shfl_sync(0xffffffffu, tid >> 5, 0);
  const int g = lane >> 2, cc = lane & 3;
  const int bid = blockIdx.x;
  const int npass = bid < 128 ? 1 : 4;
  const int dbase = bid < 128 ? bid * 4 : 512 + (bid - 128) * 16;

  const int ch = warp >> 2, n = tid & 127;
  char* cb = smem_raw + ch * SS_CH;
  const uint32_t ubar = smem_u32(smem_raw) + SSM_SMEM - 16;
  if (tid == 0) { mbar_init(ubar, 1); asm volatile("fence.mbarrier_init.release.cluster;" ::: "memory"); }
  __syncthreads();
#define CH_SYNC() asm volatile("bar.sync %0, 128;" ::"r"(ch + 1) : "memory")

#pragma unroll 1
  for (int pass = 0; pass < npass; pass++) {
    const int d0 = dbase + pass * 4;
    {
      const int idx = (d0 + ch) * N_ST + n;
      const float are = ldg_bf16(ar.Are + idx), aim = ldg_bf16(ar.Aim + idx);
      const float bre = ldg_bf16(ar.Bre + idx), bim = ldg_bf16(ar.Bim + idx);
      const float cre = ldg_bf16(ar.Cre + idx), cim = ldg_bf16(ar.Cim + idx);
      const float ldt = ldg_bf16(ar.logdt + d0 + ch), dsk = ldg_bf16(ar.Dskip + d0 + ch);
      if (tid == 0) {
        mbar_expect_tx(ubar, 32768);
#pragma unroll 1
        for (int i = 0; i < 8; i++) tma2d(smem_u32(smem_raw) + xg_off(i), &tm_x, d0 & ~7, i * 256, ubar);
      }
      if (pass == 0) {
        const uint4 z = make_uint4(0, 0, 0, 0);
        SM_U4(cb + SS_TAP + n * 16) = z;
        if (n < 104) SM_U4(cb + SS_TAP + 2048 + n * 16) = z;
        else if (n == 104) SM_U4(cb + SS_W9) = z;
        if (n < 33) SM_U4(cb + n * 16) = z;
      }
      DBG_T(7);
      const float dt = bf_round(expf(ldt));
      const float al = (dt * are) * 1.4426950408889634f, th = dt * aim;
      const float2 c0 = cmul(make_float2(cre, cim), make_float2(dt * bre, dt * bim));
      const float2 e64 = cexp_l(al, th, 64.f), e128 = csq(e64), e256 = cexp_l(al, th, 256.f), e512 = csq(e256);
      const float2 k128 = cmul(c0, e128), k256 = cmul(c0, e256), k384 = cmul(k256, e128);
      const float2 k512 = cmul(c0, e512), k516 = cmul(k512, cexp_l(al, th, 4.f));
      const float2 e1024 = cexp_l(al, th, 1024.f), k1024 = cmul(c0, e1024);
      float k2048 = fmaf(k1024.x, e1024.x, -k1024.y * e1024.y);
      char* ca = cb + SS_CONST + n * 80;
      SM_F4(ca) = make_float4(al, th, e64.x, e64.y);
      SM_F4(ca + 16) = make_float4(c0.x, c0.y, k128.x, k128.y);
      SM_F4(ca + 32) = make_float4(k256.x, k256.y, k384.x, k384.y);
      SM_F4(ca + 48) = make_float4(k512.x, k512.y, k516.x, k516.y);
      SM_F2(ca + 64) = k1024;
#pragma unroll
      for (int o = 16; o > 0; o >>= 1) k2048 += __shfl_xor_sync(~0u, k2048, o);
      if (lane == 0) SM_F32(cb + SS_KC + (warp & 3) * 2576 + 2560) = k2048;
      if (n == 0) SM_F32(cb + SS_KB + 8) = dsk;
      __syncwarp();
      DBG_T(0);
      float kd[5][4];
#pragma unroll
      for (int t = 0; t < 5; t++) { kd[t][0] = kd[t][1] = kd[t][2] = kd[t][3] = 0.f; }
      const float l1 = (float)g, l128 = (float)(128 * g);
      const char* cr = cb + SS_CONST + ((warp & 3) * 32 + cc) * 80;
      const int o2 = 32 + (g >> 2) * 8, o3 = 48 + (g & 1) * 8, s2 = ((g & 3) << 2) | cc, s3 = ((g >> 1) << 2) | cc;
#pragma unroll 2
      for (int st = 0; st < 8; st++, cr += 320) {
        const float4 q0 = *(const float4*)cr, q1 = *(const float4*)(cr + 16);
        const float2 q2 = *(const float2*)(cr + o2), q3 = *(const float2*)(cr + o3), q4 = *(const float2*)(cr + 64);
        const float2 p1 = cexp_l(q0.x, q0.y, l1), p128 = cexp_l(q0.x, q0.y, l128);
        const float2 p2 = csq(p1), p8 = csq(csq(p2));
        const float2 a1 = cmul(p8, make_float2(q0.z, q0.w));
        float2 x = cmulc(make_float2(q1.x, q1.y), p1);
        mma_tf32(kd[0], p8.x, a1.x, p8.y, a1.y, x.x, x.y);
        x = cmulc(make_float2(q1.z, q1.w), p1);
        mma_tf32(kd[1], p8.x, a1.x, p8.y, a1.y, x.x, x.y);
        x = cmulc(q2, make_float2(__shfl_sync(~0u, p2.x, s2), __shfl_sync(~0u, p2.y, s2)));
        mma_tf32(kd[2], p8.x, a1.x, p8.y, a1.y, x.x, x.y);
        x = cmulc(q3, make_float2(__shfl_sync(~0u, p128.x, s3), __shfl_sync(~0u, p128.y, s3)));
        mma_tf32(kd[3], p8.x, a1.x, p8.y, a1.y, x.x, x.y);
        x = cmulc(q4, p128);
        mma_tf32(kd[4], p8.x, a1.x, p8.y, a1.y, x.x, x.y);
      }
      char* kc = cb + SS_KC + (warp & 3) * 2576;
#pragma unroll
      for (int e = 0; e < 2; e++) {
        const int row = g + e * 8;
        SM_F2(kc + 4 * (8 * row + 2 * cc)) = make_float2(kd[0][2 * e], kd[0][2 * e + 1]);
        SM_F2(kc + 4 * (128 + 8 * row + 2 * cc)) = make_float2(kd[1][2 * e], kd[1][2 * e + 1]);
        SM_F2(kc + 4 * (256 + 64 * (cc >> 1) + 4 * row + 2 * (cc & 1))) = make_float2(kd[2][2 * e], kd[2][2 * e + 1]);
        SM_F2(kc + 4 * (384 + 32 * cc + 2 * row)) = make_float2(kd[3][2 * e], kd[3][2 * e + 1]);
        SM_F32(kc + 4 * (512 + 32 * cc + row)) = kd[4][2 * e];
        SM_F32(kc + 4 * (528 + 32 * cc + row)) = kd[4][2 * e + 1];
      }
    }
    DBG_T(8);
    uint32_t lw[9], lg[9];
    ln_load(ar.u, ar.gate_w, (bid & 127) * 16 + warp, lane, lw, lg);
    CH_SYNC();
    {
      const char* kc = cb + SS_KC;
      auto kq = [&](int idx) {
        const char* q = kc + 4 * idx;
        return (*(const float*)q + *(const float*)(q + 2576)) + (*(const float*)(q + 5152) + *(const float*)(q + 7728));
      };
#pragma unroll
      for (int it = 0; it < 5; it++) {
        const int idx = n + 128 * it;
        float t = kq(idx);
        if ((it == 1 || it == 2) && n == 127) t -= kq(idx + 1);
        if (it == 4 && n == 0) { SM_F2(cb + SS_KB) = make_float2(t, kq(640)); t = 0.f; }
        int off;
        if (it < 2) off = TP_0 + 2 * (272 - idx);
        else if (it == 2) {
          const int sel = n & 3, mu = 32 + (n >> 2);
          off = sel == 2 ? TP_W3B + 2 * (144 - mu) : (sel == 0 ? TP_W3A : sel == 1 ? TP_UA : TP_UB) + 2 * (80 - mu);
        } else if (it == 3) off = ((n & 1) ? TP_W3B : TP_W5) + 2 * (80 - (n >> 1));
        else off = ((n & 1) ? TP_W7 : TP_W9) + 2 * (80 - (n >> 1));
        const unsigned short hv = pack_bf16(t, 0.f);
        SM_U16(cb + SS_TAP + off) = hv;
        SM_U16(cb + SS_TAP + SS_TAPC + off + 2) = hv;
      }
    }
    DBG_T(11);
    if (pass == 0) {
      if (bid < 128) ln_row(bid * 16 + warp, lane, sc, lw, lg, reinterpret_cast<uint32_t*>(smem_raw + SS_XN) + warp * 288);
      asm volatile("fence.proxy.async.shared::cta;" ::: "memory");
    }
    DBG_T(12);
    mbar_wait(ubar, pass & 1);
    DBG_T(2);
    {
      const uint32_t src = smem_u32(smem_raw) + xg_off(warp >> 1) + ((warp & 1) * 128 + lane) * 16;
      const int mych = g - (d0 & 4);
      char* dst = smem_raw + mych * SS_CH + ((warp >> 1) + 1) * 528 + (warp & 1) * 256 + cc * 4;
#pragma unroll
      for (int i = 0; i < 4; i++) {
        uint32_t r[4];
        ldsm4t(r, src + i * 512);
        if (mych >= 0 && mych < 4) {
#pragma unroll
          for (int k = 0; k < 4; k++) SM_U32(dst + i * 64 + k * 16) = r[k];
        }
      }
    }
    DBG_T(9);
    __syncthreads();
    DBG_T(1);
    if (pass == 0 && bid < 128 && tid == 480) {
      asm volatile("cp.async.bulk.global.shared::cta.bulk_group [%0], [%1], %2;\ncp.async.bulk.commit_group;"
                   ::"l"(sc.xn + (size_t)bid * 16 * D_MOD), "r"(smem_u32(smem_raw) + SS_XN), "r"(18432) : "memory");
    }
    {
      DBG_T(10);
#pragma unroll 1
      for (int i = n - 1; i < 224; i += 128) {
        const char* ur = cb + ((i >> 5) + 1) * 528 + (i & 31) * 16;
        const uint4 w0 = *(const uint4*)(ur - ((i & 31) ? 16 : 32) + (i < 0 ? 16 : 0)), w1 = *(const uint4*)ur,
                    w2 = *(const uint4*)(ur + ((i & 31) == 31 ? 32 : 16));
        const uint32_t wv[12] = {w0.x, w0.y, w0.z, w0.w, w1.x, w1.y, w1.z, w1.w, w2.x, w2.y, w2.z, w2.w};
        char* o = cb + 32 + 16 * i;
        SM_U4(o + SS_UA) = make_uint4(wv[3], wv[4], wv[5], wv[6]);
        SM_U4(o + SS_UB) = make_uint4(wv[1], wv[2], wv[3], wv[4]);
        float v[22], wa[16];
#pragma unroll
        for (int k = 1; k < 11; k++) { v[2 * k] = bf_lo(wv[k]); v[2 * k + 1] = bf_hi(wv[k]); }
#pragma unroll
        for (int k = 4; k < 16; k++) wa[k] = (v[k - 1] + v[k]) + v[k + 1];
        SM_U4(o + SS_W3A) = make_uint4(pack_bf16(wa[8], wa[9]), pack_bf16(wa[10], wa[11]), pack_bf16(wa[12], wa[13]), pack_bf16(wa[14], wa[15]));
        SM_U4(o + SS_W3B) = make_uint4(pack_bf16(wa[4], wa[5]), pack_bf16(wa[6], wa[7]), pack_bf16(wa[8], wa[9]), pack_bf16(wa[10], wa[11]));
        if (i < 192) {
#pragma unroll
          for (int k = 8; k < 16; k++) wa[k] += v[k - 2] + v[k + 2];
          SM_U4(o + SS_W5) = make_uint4(pack_bf16(wa[8], wa[9]), pack_bf16(wa[10], wa[11]), pack_bf16(wa[12], wa[13]), pack_bf16(wa[14], wa[15]));
          if (i < 128) {
#pragma unroll
            for (int k = 8; k < 16; k++) wa[k] += v[k - 3] + v[k + 3];
            SM_U4(o + SS_W7) = make_uint4(pack_bf16(wa[8], wa[9]), pack_bf16(wa[10], wa[11]), pack_bf16(wa[12], wa[13]), pack_bf16(wa[14], wa[15]));
#pragma unroll
            for (int k = 8; k < 16; k++) wa[k] += v[k - 4] + v[k + 4];
            SM_U4(o + SS_W9) = make_uint4(pack_bf16(wa[8], wa[9]), pack_bf16(wa[10], wa[11]), pack_bf16(wa[12], wa[13]), pack_bf16(wa[14], wa[15]));
          }
        }
      }
    }
    CH_SYNC();
    DBG_T(3);
    {
      const int role = (warp + ch) & 3;
      const char* tp = cb + SS_TAP + ((g & 1) ? SS_TAPC + 2 : 0) - 2 * (g - 2 * cc);
      if (role < 2) {
        uint32_t ta[17][4];
#pragma unroll
        for (int k = 0; k < 17; k++) load_tquad(ta[k], tp + TP_0 + 544, k);
        float acc[8][4];
#pragma unroll
        for (int i = 0; i < 8; i++) { acc[i][0] = acc[i][1] = acc[i][2] = acc[i][3] = 0.f; }
        const uint32_t bpos = smem_u32(cb) + ((lane & 7) + 1) * 528 + role * 256 + (lane >> 3) * 16;
        const uint32_t bmid = role ? bpos : bpos - 16;
#pragma unroll
        for (int j2 = -16; j2 < 8; j2 += 2) {
          uint32_t b[4];
          ldsm4(b, (j2 < -8 ? bpos - 16 : j2 < 0 ? bmid : bpos) + 32 * j2);
#pragma unroll
          for (int hf = 0; hf < 2; hf++) {
#pragma unroll
            for (int i = 0; i < 8; i++) {
              const int k = i - j2 - hf;
              if (k >= 0 && k <= 16) mma_bf16(acc[i], ta[k][0], ta[k][1], ta[k][2], ta[k][3], b[2 * hf], b[2 * hf + 1]);
            }
          }
        }
        char* ya = cb + SS_Y + 4 * (520 * cc + 128 * role + g);
#pragma unroll
        for (int i = 0; i < 8; i++) {
          SM_F32(ya + 64 * i) = acc[i][0]; SM_F32(ya + 64 * i + 1040) = acc[i][1];
          SM_F32(ya + 64 * i + 32) = acc[i][2]; SM_F32(ya + 64 * i + 1072) = acc[i][3];
        }
      } else if (role == 2) {
        p8_tiles<1, 11>(cb, tp, lane);
      } else {
        p8_tiles<11, 16>(cb, tp, lane);
#pragma unroll 1
        for (int hh = 0; hh < 2; hh++) {
          float acc[5][4];
#pragma unroll
          for (int i = 0; i < 5; i++) { acc[i][0] = acc[i][1] = acc[i][2] = acc[i][3] = 0.f; }
          const uint32_t za = smem_u32(cb), sa = za + 32 + lane * 32 + hh * 16;
          band<3, 8, 4, 9, -1, 32>(acc, tp + TP_W9 + 288, sa + SS_W9, za, lane);
          band<3, 8, 4, 9, 0, 32>(acc, tp + TP_W7 + 288, sa + SS_W7 - 16, za, lane);
          char* a = cb + SS_Y + 2 * SS_YB + 4 * (16 * g + 8 * hh + 2 * cc);
#pragma unroll
          for (int I = 3; I < 8; I++) {
            SM_F2(a + 1040 * (I - 3)) = make_float2(acc[I - 3][0], acc[I - 3][1]);
            SM_F2(a + 1040 * (I - 3) + 512) = make_float2(acc[I - 3][2], acc[I - 3][3]);
          }
        }
      }
    }
    CH_SYNC();
    DBG_T(4);
    if (pass == 0 && bid < 128 && tid == 480) {
      asm volatile("cp.async.bulk.wait_group 0;\nfence.acq_rel.gpu;" ::: "memory");
      atomicAdd(&sc.lnflag[(bid >> 3) * 2], 1u);
    }
    {
      const float4 kb = SM_F4(cb + SS_KB);
      const uint32_t dk = pack_bf16(kb.z, kb.z);
#pragma unroll
      for (int k = 0; k < 4; k++) {
        const int t0 = n * 4 + 512 * k;
        char* ya = cb + SS_Y + 4 * (t0 + 4 * (t0 >> 8));
        float4 y = SM_F4(ya);
        if (k > 0 || t0 >= 128) { const float4 b = SM_F4(ya + SS_YB); y.x += b.x; y.y += b.y; y.z += b.z; y.w += b.w; }
        if (k > 1 || (k == 1 && t0 >= 768)) {
          const float4 b = SM_F4(ya + 2 * SS_YB - 3120);
          y.x += b.x; y.y += b.y; y.z += b.z; y.w += b.w;
          if (k > 1 || t0 >= 1020) {
            const char* wp = cb + SS_W7 + 32 + 2 * (t0 - 1026);
            const uint32_t wl = *(const uint32_t*)wp, wm = *(const uint32_t*)(wp + 4), wh = *(const uint32_t*)(wp + 8);
            y.x = fmaf(kb.x, bf_hi(wl), y.x); y.y = fmaf(kb.x, bf_lo(wm), y.y);
            y.z = fmaf(kb.x, bf_hi(wm), y.z); y.w = fmaf(kb.x, bf_lo(wh), y.w);
            if (k == 3 && n == 127) {
              const uint2 u03 = SM_U2(cb + 528);
              float pre = bf_lo(u03.x);
              y.x = fmaf(kb.y, pre, y.x); pre += bf_hi(u03.x);
              y.y = fmaf(kb.y, pre, y.y); pre += bf_lo(u03.y);
              y.z = fmaf(kb.y, pre, y.z); pre += bf_hi(u03.y);
              y.w = fmaf(kb.y, pre, y.w);
            }
          }
        }
        const uint2 uu = SM_U2(cb + ((t0 >> 8) + 1) * 528 + (t0 & 255) * 2);
        uint2 o;
        o.x = bf2_add(pack_bf16(y.x, y.y), bf2_mul(uu.x, dk));
        o.y = bf2_add(pack_bf16(y.z, y.w), bf2_mul(uu.y, dk));
        *reinterpret_cast<uint2*>(sc.aT + (size_t)(d0 + ch) * L_SEQ + t0) = o;
      }
    }
    DBG_T(5);
    if (pass + 1 < npass) { asm volatile("fence.proxy.async.shared::cta;" ::: "memory"); __syncthreads(); }
  }
  DBG_T(6);
  DBG_G(31);
}

constexpr int XS_BYTES = 9 * 16384;
constexpr int STAGE_BYTES = 12288;
constexpr int NSTAGE = 6;
constexpr int OFF_ST = XS_BYTES;
constexpr int OFF_B1 = OFF_ST + NSTAGE * STAGE_BYTES;
constexpr int OFF_B2 = OFF_B1 + 1152;
constexpr int OFF_BAR = OFF_B2 + 1152;
constexpr int B_FULL = 0, B_X = 48  , B_RB = 120  , B_OWN = 152, B_FIN = 160,
              B_EMPTY = 168  , B_TS = 216  , B_TS8 = 248, B_TR = 256  , B_P1L = 280, B_P1R = 288, NBARS = 37;
constexpr int MLP_SMEM = OFF_BAR + 512 + 1024;
constexpr int OFF_STG = 65536, OFF_C8 = 131072;

struct MlpCtx {
  uint32_t bars;
  uint32_t dA, dB;
  int lane;
};
__device__ __forceinline__ void stage_release(const MlpCtx& c, int slot) {
  if (c.lane == 0) mbar_arrive(c.bars + B_EMPTY + 8 * slot);
}
template <int P>
__device__ __forceinline__ void gelu_part(uint32_t baddr, float (&acc)[48]) {
  asm volatile("" : R8(acc, P * 8)::"memory");
  uint32_t b0 = lds32(baddr + P * 32), b1 = lds32(baddr + P * 32 + 16);
  uint32_t r0 = gelu_pack(acc[P * 8 + 0], acc[P * 8 + 1], b0);
  uint32_t r1 = gelu_pack(acc[P * 8 + 2], acc[P * 8 + 3], b0);
  uint32_t r2 = gelu_pack(acc[P * 8 + 4], acc[P * 8 + 5], b1);
  uint32_t r3 = gelu_pack(acc[P * 8 + 6], acc[P * 8 + 7], b1);
  acc[P * 8 + 0] = __uint_as_float(r0);
  acc[P * 8 + 1] = __uint_as_float(r1);
  acc[P * 8 + 2] = __uint_as_float(r2);
  acc[P * 8 + 3] = __uint_as_float(r3);
}
__device__ __forceinline__ void h_push(uint32_t (&h)[144], float (&acc)[48]) {
#pragma unroll
  for (int i = 0; i < 72; i++) h[i] = h[i + 24];
#pragma unroll
  for (int i = 0; i < 24; i++) h[72 + i] = __float_as_uint(acc[(i >> 2) * 8 + (i & 3)]);
}
template <int SB, int I>
__device__ __forceinline__ void p1_mma(const MlpCtx& c, float (&cur)[48]) {
  constexpr int S = SB % 9;
  wgmma_ss_n96<(S | I) != 0, ((S * 16384 + I * 32) >> 4),
               (4096 >> 4 << 16) + (((SB % 6) * STAGE_BYTES + I * 1024) >> 4)>(cur, c.dA, c.dB);
}
template <int SB>
__device__ __forceinline__ void p1_stage(const MlpCtx& c, int j, uint32_t baddr, float (&cur)[48], float (&prev)[48]) {
  constexpr int S = SB % 9;
  if (SB < 9) mbar_wait(c.bars + B_X + 8 * S, 0);
  mbar_wait(c.bars + B_FULL + 8 * (SB % 6), ((SB / 6) + j) & 1);
  WG_FENCE();
  p1_mma<SB, 0>(c, cur); p1_mma<SB, 1>(c, cur); p1_mma<SB, 2>(c, cur); p1_mma<SB, 3>(c, cur);
  WG_COMMIT();
  if (S >= 1 && S <= 6) gelu_part<(S >= 1 && S <= 6) ? S - 1 : 0>(baddr, prev);
  wg_wait<1>();
  if (SB > 0 || j > 0) stage_release(c, (SB + 5) % 6);
  if (S == 0) fence_regs(prev);
}
template <int SB0>
__device__ __forceinline__ void p1_chunk(const MlpCtx& c, int j, uint32_t baddr, float (&cur)[48], float (&prev)[48]) {
  p1_stage<SB0 + 0>(c, j, baddr, cur, prev); p1_stage<SB0 + 1>(c, j, baddr, cur, prev);
  p1_stage<SB0 + 2>(c, j, baddr, cur, prev); p1_stage<SB0 + 3>(c, j, baddr, cur, prev);
  p1_stage<SB0 + 4>(c, j, baddr, cur, prev); p1_stage<SB0 + 5>(c, j, baddr, cur, prev);
  p1_stage<SB0 + 6>(c, j, baddr, cur, prev); p1_stage<SB0 + 7>(c, j, baddr, cur, prev);
  p1_stage<SB0 + 8>(c, j, baddr, cur, prev);
}
template <int S, int I>
__device__ __forceinline__ void p2_one(const MlpCtx& c, float (&cur)[32], uint32_t (&h)[144]) {
  constexpr int kk = 6 * S + I;
  wgmma_rs_n64<(S | I) != 0, ((S * STAGE_BYTES + I * 2048) >> 4)>(cur, h[4 * kk], h[4 * kk + 1], h[4 * kk + 2], h[4 * kk + 3], c.dB);
}
template <int S>
__device__ __forceinline__ void p2_mma(const MlpCtx& c, uint32_t parity, float (&cur)[32], uint32_t (&h)[144]) {
  mbar_wait(c.bars + B_FULL + 8 * S, parity);
  WG_FENCE();
  p2_one<S, 0>(c, cur, h); p2_one<S, 1>(c, cur, h); p2_one<S, 2>(c, cur, h);
  p2_one<S, 3>(c, cur, h); p2_one<S, 4>(c, cur, h); p2_one<S, 5>(c, cur, h);
  WG_COMMIT();
}
__device__ __forceinline__ int chunk_of(int pos, int pr, int rank) {
  const int off = (int)(0x03231201ull >> (4 * pos)) & 3;
  const int mine = (0x168 >> pos) & 1;
  return pos == 1 ? 8 : 2 * ((pr + off) & 3) + (mine ? rank : rank ^ 1);
}
__device__ __forceinline__ void bulk_s2peer(uint32_t rdst, uint32_t src, uint32_t bytes, uint32_t rbar) {
  asm volatile("cp.async.bulk.shared::cluster.shared::cta.mbarrier::complete_tx::bytes [%0], [%1], %2, [%3];"
               ::"r"(rdst), "r"(src), "r"(bytes), "r"(rbar) : "memory");
}
__device__ __forceinline__ void bulk_s2g(void* gdst, uint32_t src, uint32_t bytes) {
  asm volatile("cp.async.bulk.global.shared::cta.bulk_group [%0], [%1], %2;" ::"l"(gdst), "r"(src), "r"(bytes) : "memory");
}
__device__ __forceinline__ void bulk_s2g_read_done() {
  asm volatile("cp.async.bulk.commit_group;\ncp.async.bulk.wait_group.read 0;" ::: "memory");
}
__device__ __forceinline__ void bulk_s2g_finish() {
  asm volatile("cp.async.bulk.commit_group;\ncp.async.bulk.wait_group 0;\nfence.acq_rel.gpu;" ::: "memory");
}

__global__ void __cluster_dims__(2, 1, 1) __launch_bounds__(384, 1)
mlp_kernel(const __grid_constant__ CUtensorMap tm_w1, const __grid_constant__ CUtensorMap tm_w2,
           const __grid_constant__ CUtensorMap tm_aT, const __grid_constant__ CUtensorMap tm_xn,
           const __grid_constant__ CUtensorMap tm_out,
           const __nv_bfloat16* __restrict__ w1, const __nv_bfloat16* __restrict__ w2,
           const __nv_bfloat16* __restrict__ b1, const __nv_bfloat16* __restrict__ b2, __nv_bfloat16* __restrict__ out,
           const Scratch sc) {
  extern __shared__ __align__(1024) char smem_raw[];
  DBG_G(28);
  const uint32_t sb = (smem_u32(smem_raw) + 1023) & ~1023u;
  const uint32_t bars = sb + OFF_BAR;
  const int tid = threadIdx.x, lane = tid & 31;
  const int warp = __shfl_sync(0xffffffffu, tid >> 5, 0), wg = warp >> 2;
  const int m = blockIdx.x >> 3, f = blockIdx.x & 7, rank = f & 1, pr = f >> 1;

  if (lane == 0) {
    if (warp == 8) {
#pragma unroll
      for (int i = 0; i < B_EMPTY / 8; i++) mbar_init(bars + i * 8, 1);
      asm volatile("fence.mbarrier_init.release.cluster;" ::: "memory");
#pragma unroll
      for (int i = 0; i < 4; i++) mbar_expect_tx(bars + B_RB + 8 * i, 16384);
    } else if (warp == 9) {
#pragma unroll
      for (int i = B_EMPTY / 8; i < NBARS; i++) mbar_init(bars + i * 8, 8);
      asm volatile("fence.mbarrier_init.release.cluster;" ::: "memory");
    } else if (warp == 10) {
      asm volatile("prefetch.tensormap [%0];" ::"l"(&tm_w1) : "memory");
      asm volatile("prefetch.tensormap [%0];" ::"l"(&tm_xn) : "memory");
    } else if (warp == 11) {
      asm volatile("prefetch.tensormap [%0];" ::"l"(&tm_w2) : "memory");
      asm volatile("prefetch.tensormap [%0];" ::"l"(&tm_aT) : "memory");
      asm volatile("prefetch.tensormap [%0];" ::"l"(&tm_out) : "memory");
    }
  }
  __syncthreads();
  DBG_T(7);
  const uint32_t rdelta = mapa(sb, rank ^ 1) - sb;

  if (wg == 2) {
    asm volatile("setmaxnreg.dec.sync.aligned.u32 " PREGS ";");
    const int pw = warp - 8;
    if (lane == 0 && pw == 3) DBG_H(6);
    if (pw < 2) {
      int slot = pw, par = 1, it = pw;
      auto w1_item = [&]() {
        const int ch = it / 9, s = it - ch * 9;
        const uint32_t dst = sb + OFF_ST + slot * STAGE_BYTES, fb = bars + B_FULL + 8 * slot;
        mbar_wait(bars + B_EMPTY + 8 * slot, par);
        mbar_expect_tx(fb, STAGE_BYTES);
        tma2d(dst, &tm_w1, f * 576 + ch * 96, s * 64, fb);
        tma2d(dst + 4096, &tm_w1, f * 576 + ch * 96 + 32, s * 64, fb);
        tma2d(dst + 8192, &tm_w1, f * 576 + ch * 96 + 64, s * 64, fb);
        it += 2;
        slot += 2;
        if (slot >= 6) { slot -= 6; par ^= 1; }
      };
      if (lane == 0) {
#pragma unroll 1
        while (it < 6) w1_item();
      }
      __syncwarp();
      asm volatile("barrier.cluster.arrive.relaxed.aligned;" ::: "memory");
      if (lane == 0) {
#pragma unroll 1
        while (it < 54) w1_item();
#pragma unroll 1
        for (int pos = 0; pos < 9; pos++) {
          const int chunk = chunk_of(pos, pr, rank);
#pragma unroll 1
          for (slot = pw; slot < 6; slot += 2) {
            const uint32_t fb = bars + B_FULL + 8 * slot;
            mbar_wait(bars + B_EMPTY + 8 * slot, par);
            mbar_expect_tx(fb, STAGE_BYTES);
            tma2d(sb + OFF_ST + slot * STAGE_BYTES, &tm_w2, chunk * 64, f * 576 + slot * 96, fb);
          }
          par ^= 1;
        }
        if (pw == 0) {
          mbar_wait(bars + B_EMPTY, par);
          mbar_wait(bars + B_EMPTY + 8, par);
          asm volatile("griddepcontrol.wait;" ::: "memory");
          mbar_expect_tx(bars + B_FULL, 16384 + 2048);
          tma2d(sb + OFF_ST, &tm_aT, m * 128, f * 64, bars + B_FULL);
          tma2d(sb + OFF_ST + 8192, &tm_aT, m * 128 + 64, f * 64, bars + B_FULL);
#pragma unroll 1
          for (int i = 0; i < 8; i++)
            bulk_g2s(sb + OFF_ST + 16384 + i * 256, sc.aT + (size_t)(512 + f * 8 + i) * L_SEQ + m * 128, 256, bars + B_FULL);
        }
      }
      __syncwarp();
      asm volatile("barrier.cluster.wait.acquire.aligned;" ::: "memory");
    } else if (pw == 2) {
      if (lane == 0) {
        wait_flag(&sc.lnflag[m * 2], 8);
        DBG_X(1);
#pragma unroll 1
        for (int kb = 0; kb < 9; kb++) {
          mbar_expect_tx(bars + B_X + 8 * kb, kb == 1 ? 16384 + 2304 : 16384);
          tma2d(sb + kb * 16384, &tm_xn, kb * 64, m * 128, bars + B_X + 8 * kb);
          if (kb == 1) {
            bulk_g2s(sb + OFF_B1, b1 + f * 576, 1152, bars + B_X + 8);
            bulk_g2s(sb + OFF_B2, b2, 1152, bars + B_X + 8);
          }
        }
        DBG_X(3);
        if (atomicAdd(&sc.lnflag[m * 2 + 1], 1u) == 7) { sc.lnflag[m * 2] = 0; sc.lnflag[m * 2 + 1] = 0; }
      }
      __syncwarp();
      asm volatile("barrier.cluster.arrive.relaxed.aligned;" ::: "memory");
      asm volatile("barrier.cluster.wait.acquire.aligned;" ::: "memory");
      if (lane == 0) {
        mbar_wait(bars + B_P1R, 0);
#pragma unroll 1
        for (int k = 0; k < 4; k++) {
          mbar_wait(bars + B_TS + 8 * k, 0);
          bulk_s2peer(sb + k * 16384 + rdelta, sb + OFF_STG + k * 16384, 16384, bars + B_RB + 8 * k + rdelta);
        }
#pragma unroll 1
        for (int k = 0; k < 4; k++) mbar_wait(bars + B_RB + 8 * k, 0);
        mbar_arrive_remote(bars + B_FIN + rdelta);
        mbar_wait(bars + B_FIN, 0);
      }
    } else {
      if (lane == 0) {
#pragma unroll 1
        for (int i = 0; i < 36; i++)
          asm volatile("cp.async.bulk.prefetch.L2.global [%0], %1;"
                       ::"l"(w1 + (size_t)(m * 36 + i) * F_HID + f * 576), "r"(1152) : "memory");
        asm volatile("cp.async.bulk.prefetch.L2.global [%0], %1;"
                     ::"l"(w2 + (size_t)(f * 576 + m * 36) * D_MOD), "r"(36 * 1152) : "memory");
      }
      __syncwarp();
      asm volatile("barrier.cluster.arrive.relaxed.aligned;" ::: "memory");
      asm volatile("barrier.cluster.wait.acquire.aligned;" ::: "memory");
      if (lane == 0) {
        mbar_wait(bars + B_TS8, 0);
        bulk_s2g(sc.slots8 + (size_t)(m * 8 + f) * 4096, sb + OFF_C8, 16384);
        bulk_s2g_finish();
#pragma unroll 1
        for (int i = 0; i < 8; i++) atomicAdd(&sc.flags[m * 16 + 8 + i], 1u);
#pragma unroll 1
        for (int k = 0; k < 3; k++) {
          const int chunk = 2 * ((pr + k + 1) & 3) + rank;
          mbar_wait(bars + B_TR + 8 * k, 0);
          bulk_s2g(sc.slots + (size_t)((m * 8 + chunk) * 3 + k) * 4096, sb + k * 16384, 16384);
          bulk_s2g_finish();
          atomicAdd(&sc.flags[m * 16 + chunk], 1u);
          DBG_H(16 + k);
          if (k == 0) {
            mbar_expect_tx(bars + B_OWN, 65536);
            wait_flag(&sc.flags[m * 16 + 8 + f], 8);
            sc.flags[m * 16 + 8 + f] = 0;
#pragma unroll 1
            for (int i = 0; i < 8; i++)
              bulk_g2s(sb + OFF_C8 + i * 2048, sc.slots8 + (size_t)(m * 8 + i) * 4096 + f * 512, 2048, bars + B_OWN);
          }
        }
        wait_flag(&sc.flags[m * 16 + f], 3);
        sc.flags[m * 16 + f] = 0;
        bulk_g2s(sb, sc.slots + (size_t)((m * 8 + f) * 3) * 4096, 49152, bars + B_OWN);
        DBG_H(19);
      }
    }
  } else {
    DBG_T(1);
    asm volatile("setmaxnreg.inc.sync.aligned.u32 " CREGS ";");
    const int wi = warp & 3;
    DBG_T(0);
    MlpCtx c;
    c.bars = bars; c.lane = lane;
    c.dA = (((sb + wg * 8192) & 0x3FFFF) >> 4) | (1u << 16);
    c.dB = ((sb + OFF_ST) & 0x3FFFF) >> 4;

    uint32_t h[144];
    float acc2a[32], acc2b[32];
    {
      float accA[48], accB[48];
#pragma unroll
      for (int i = 0; i < 48; i++) { accA[i] = 0.f; accB[i] = 0.f; }
#pragma unroll
      for (int i = 0; i < 144; i++) h[i] = 0;
      uint32_t baddr = sb + OFF_B1 + (lane & 3) * 4 - 192;
#pragma unroll 1
      for (int j = 0; j < 3; j++) {
        DBG_T(11 + 2 * j);
        h_push(h, accA);
        p1_chunk<0>(c, j, baddr, accA, accB);
        baddr += 192;
        DBG_T(10 + 2 * j);
        h_push(h, accB);
        p1_chunk<9>(c, j, baddr, accB, accA);
        baddr += 192;
        if (j == 0) asm volatile("barrier.cluster.arrive.relaxed.aligned;" ::: "memory");
      }
#pragma unroll
      for (int i = 0; i < 24; i++) h[96 + i] = __float_as_uint(accA[(i >> 2) * 8 + (i & 3)]);
      DBG_T(2);
      p2_mma<0>(c, 1, acc2a, h);
      wg_wait<1>();
      stage_release(c, 5);
      fence_regs(accB);
      asm volatile("barrier.cluster.wait.acquire.aligned;" ::: "memory");
      if (lane == 0) { mbar_arrive(bars + B_P1L); mbar_arrive_remote(bars + B_P1R + rdelta); }
      p2_mma<1>(c, 1, acc2a, h);
      gelu_part<0>(baddr, accB); gelu_part<1>(baddr, accB);
      wg_wait<1>(); stage_release(c, 0);
      p2_mma<2>(c, 1, acc2a, h);
      gelu_part<2>(baddr, accB); gelu_part<3>(baddr, accB);
      wg_wait<1>(); stage_release(c, 1);
      p2_mma<3>(c, 1, acc2a, h);
      gelu_part<4>(baddr, accB);
      wg_wait<1>(); stage_release(c, 2);
      p2_mma<4>(c, 1, acc2a, h);
      gelu_part<5>(baddr, accB);
#pragma unroll
      for (int i = 0; i < 24; i++) h[120 + i] = __float_as_uint(accB[(i >> 2) * 8 + (i & 3)]);
      wg_wait<1>(); stage_release(c, 3);
      p2_mma<5>(c, 1, acc2a, h);
      wg_wait<1>(); stage_release(c, 4);
    }
    const uint32_t lbuf = sb + warp * 2048 + lane * 16;
    mbar_wait(bars + B_P1L, 0);
#pragma unroll 1
    for (int pos = 0; pos < 8; pos++) {
      const bool recv = (0x68 >> pos) & 1;
      const int k = recv ? (pos - 2) >> 1 : (pos + 1) >> 1;
      const int ks = k > 3 ? 3 : k;
      const uint32_t addr = lbuf + ks * 16384 + (recv ? 0 : OFF_STG);
      const uint32_t sig = bars + (recv ? B_TR + 8 * k : pos == 1 ? B_TS8 : B_TS + 8 * ks);
      if (recv) mbar_wait(bars + B_RB + k * 8, 0);
      wg_wait<0>(); stage_release(c, 5);
      fence_regs(acc2a);
      DBG_T(20 + pos);
      if (recv) {
#pragma unroll
        for (int i = 0; i < 4; i++) {
          const float4 r = lds128f(addr + i * 512);
          const uint32_t w0 = __float_as_uint(r.x), w1 = __float_as_uint(r.y), w2 = __float_as_uint(r.z), w3 = __float_as_uint(r.w);
          acc2a[8 * i + 0] += bf_lo(w0); acc2a[8 * i + 1] += bf_hi(w0); acc2a[8 * i + 2] += bf_lo(w1); acc2a[8 * i + 3] += bf_hi(w1);
          acc2a[8 * i + 4] += bf_lo(w2); acc2a[8 * i + 5] += bf_hi(w2); acc2a[8 * i + 6] += bf_lo(w3); acc2a[8 * i + 7] += bf_hi(w3);
        }
      }
      if (pos == 1) {
        const uint32_t a8 = sb + OFF_C8 + warp * 256 + lane * 8;
#pragma unroll
        for (int q = 0; q < 8; q++)
          asm volatile("st.shared.v2.u32 [%0], {%1,%2};" ::"r"(a8 + q * 2048), "r"(pack_bf16(acc2a[4 * q], acc2a[4 * q + 1])),
                       "r"(pack_bf16(acc2a[4 * q + 2], acc2a[4 * q + 3])) : "memory");
      } else {
#pragma unroll
        for (int i = 0; i < 4; i++)
          sts128(addr + i * 512, pack_bf16(acc2a[8 * i], acc2a[8 * i + 1]), pack_bf16(acc2a[8 * i + 2], acc2a[8 * i + 3]),
                 pack_bf16(acc2a[8 * i + 4], acc2a[8 * i + 5]), pack_bf16(acc2a[8 * i + 6], acc2a[8 * i + 7]));
      }
      const uint32_t par = pos & 1;
      p2_mma<0>(c, par, acc2a, h);
      asm volatile("fence.proxy.async.shared::cta;" ::: "memory");
      __syncwarp();
      if (lane == 0) mbar_arrive(sig);
      p2_mma<1>(c, par, acc2a, h);
      wg_wait<1>(); stage_release(c, 0);
      p2_mma<2>(c, par, acc2a, h);
      wg_wait<1>(); stage_release(c, 1);
      p2_mma<3>(c, par, acc2a, h);
      wg_wait<1>(); stage_release(c, 2);
      p2_mma<4>(c, par, acc2a, h);
      wg_wait<1>(); stage_release(c, 3);
      p2_mma<5>(c, par, acc2a, h);
      wg_wait<1>(); stage_release(c, 4);
    }
    DBG_T(3);
    {
      const int g = lane >> 2, cc = lane & 3;
      const int t0 = m * 128 + warp * 16 + g;
      const uint2 ga = __ldcg(&sc.gate[t0]), gb = __ldcg(&sc.gate[t0 + 8]);
#pragma unroll
      for (int i = 0; i < 32; i++) acc2b[i] = 0.f;
      mbar_wait(bars + B_RB + 24, 0);
      mbar_wait(bars + B_OWN, 0);
      DBG_T(8);
#pragma unroll
      for (int k = 0; k < 4; k++) {
#pragma unroll
        for (int i = 0; i < 4; i++) {
          float4 r = lds128f(lbuf + k * 16384 + i * 512);
          const uint32_t w0 = __float_as_uint(r.x), w1 = __float_as_uint(r.y), w2 = __float_as_uint(r.z), w3 = __float_as_uint(r.w);
          acc2b[8 * i + 0] += bf_lo(w0); acc2b[8 * i + 1] += bf_hi(w0); acc2b[8 * i + 2] += bf_lo(w1); acc2b[8 * i + 3] += bf_hi(w1);
          acc2b[8 * i + 4] += bf_lo(w2); acc2b[8 * i + 5] += bf_hi(w2); acc2b[8 * i + 6] += bf_lo(w3); acc2b[8 * i + 7] += bf_hi(w3);
        }
      }
      float c8[4] = {0.f, 0.f, 0.f, 0.f};
#pragma unroll
      for (int i = 0; i < 8; i++) {
        uint32_t w0, w1;
        asm volatile("ld.shared.v2.u32 {%0,%1}, [%2];" : "=r"(w0), "=r"(w1) : "r"(sb + OFF_C8 + i * 2048 + warp * 256 + lane * 8));
        c8[0] += bf_lo(w0); c8[1] += bf_hi(w0); c8[2] += bf_lo(w1); c8[3] += bf_hi(w1);
      }
      DBG_T(9);
      mbar_wait(bars + B_FULL, 0);
      __nv_bfloat16* op = out + (size_t)t0 * D_MOD + cc * 2;
      {
        uint32_t a0, a1;
        const uint32_t addr = sb + OFF_ST + 16384 + (lane & 7) * 256 + (warp * 2 + ((lane >> 3) & 1)) * 16;
        asm volatile("ldmatrix.sync.aligned.m8n8.x2.trans.shared.b16 {%0,%1}, [%2];" : "=r"(a0), "=r"(a1) : "r"(addr));
        const uint32_t bb = lds32(sb + OFF_B2 + (512 + f * 8 + cc * 2) * 2);
        const uint32_t v0 = bf2_add(pack_bf16(c8[0], c8[1]), bb), v1 = bf2_add(pack_bf16(c8[2], c8[3]), bb);
        *reinterpret_cast<uint32_t*>(op + 512 + f * 8) = bf2_add(bf2_mul(ga.x, a0), bf2_mul(ga.y, v0));
        *reinterpret_cast<uint32_t*>(op + 8 * D_MOD + 512 + f * 8) = bf2_add(bf2_mul(gb.x, a1), bf2_mul(gb.y, v1));
      }
      wg_wait<0>();
      fence_regs(acc2a);
      DBG_T(4);
#pragma unroll
      for (int jj = 0; jj < 4; jj++) {
        uint32_t a[4];
        {
          const int dl = 8 * (2 * jj + (lane >> 4)) + (lane & 7);
          const int ch = 2 * wi + ((lane >> 3) & 1);
          uint32_t addr = sb + OFF_ST + wg * 8192 + dl * 128 + ((ch ^ (dl & 7)) << 4);
          asm volatile("ldmatrix.sync.aligned.m8n8.x4.trans.shared.b16 {%0,%1,%2,%3}, [%4];"
                       : "=r"(a[0]), "=r"(a[1]), "=r"(a[2]), "=r"(a[3]) : "r"(addr));
        }
        uint32_t o[4];
#pragma unroll
        for (int e = 0; e < 2; e++) {
          const int q = 2 * jj + e;
          uint32_t bb = lds32(sb + OFF_B2 + (f * 64 + q * 8 + cc * 2) * 2);
          uint32_t v0 = bf2_add(pack_bf16(acc2a[4 * q] + acc2b[4 * q], acc2a[4 * q + 1] + acc2b[4 * q + 1]), bb);
          uint32_t v1 = bf2_add(pack_bf16(acc2a[4 * q + 2] + acc2b[4 * q + 2], acc2a[4 * q + 3] + acc2b[4 * q + 3]), bb);
          o[2 * e] = bf2_add(bf2_mul(ga.x, a[2 * e]), bf2_mul(ga.y, v0));
          o[2 * e + 1] = bf2_add(bf2_mul(gb.x, a[2 * e + 1]), bf2_mul(gb.y, v1));
        }
        {
          const int row = (lane & 7) + ((lane >> 3) & 1) * 8;
          const uint32_t addr = sb + 49152 + warp * 2048 + row * 128 + (((2 * jj + (lane >> 4)) ^ (row & 7)) << 4);
          asm volatile("stmatrix.sync.aligned.m8n8.x4.shared.b16 [%0], {%1,%2,%3,%4};"
                       ::"r"(addr), "r"(o[0]), "r"(o[1]), "r"(o[2]), "r"(o[3]) : "memory");
        }
      }
      asm volatile("fence.proxy.async.shared::cta;" ::: "memory");
      __syncwarp();
      if (lane == 0) {
        asm volatile("cp.async.bulk.tensor.2d.global.shared::cta.bulk_group [%0, {%2, %3}], [%1];\n"
                     "cp.async.bulk.commit_group;\ncp.async.bulk.wait_group.read 0;"
                     ::"l"(&tm_out), "r"(sb + 49152 + warp * 2048), "r"(f * 64), "r"(m * 128 + warp * 16) : "memory");
      }
      DBG_T(5);
      DBG_G(29);
    }
  }
}

typedef CUresult (*EncodeTiledFn)(CUtensorMap*, CUtensorMapDataType, cuuint32_t, void*, const cuuint64_t*,
                                  const cuuint64_t*, const cuuint32_t*, const cuuint32_t*, CUtensorMapInterleave,
                                  CUtensorMapSwizzle, CUtensorMapL2promotion, CUtensorMapFloatOOBfill);

static void make_map(EncodeTiledFn enc, CUtensorMap* tm, void* base, uint64_t inner, uint64_t outer, uint32_t binner,
                     uint32_t bouter, CUtensorMapSwizzle swz) {
  cuuint64_t gd[2] = {inner, outer};
  cuuint64_t gs[1] = {inner * 2};
  cuuint32_t bd[2] = {binner, bouter};
  cuuint32_t es[2] = {1, 1};
  enc(tm, CU_TENSOR_MAP_DATA_TYPE_BFLOAT16, 2, base, gd, gs, bd, es, CU_TENSOR_MAP_INTERLEAVE_NONE, swz,
      CU_TENSOR_MAP_L2_PROMOTION_L2_128B, CU_TENSOR_MAP_FLOAT_OOB_FILL_NONE);
}

extern "C" void kernel_launch(void* const* d_in, const int* in_sizes, int n_in, void* d_out, int out_size) {
  const __nv_bfloat16* u = (const __nv_bfloat16*)d_in[0];
  const __nv_bfloat16* Are = (const __nv_bfloat16*)d_in[1];
  const __nv_bfloat16* Aim = (const __nv_bfloat16*)d_in[2];
  const __nv_bfloat16* Bre = (const __nv_bfloat16*)d_in[3];
  const __nv_bfloat16* Bim = (const __nv_bfloat16*)d_in[4];
  const __nv_bfloat16* Cre = (const __nv_bfloat16*)d_in[5];
  const __nv_bfloat16* Cim = (const __nv_bfloat16*)d_in[6];
  const __nv_bfloat16* logdt = (const __nv_bfloat16*)d_in[7];
  const __nv_bfloat16* Dskip = (const __nv_bfloat16*)d_in[8];
  const __nv_bfloat16* w1 = (const __nv_bfloat16*)d_in[10];
  const __nv_bfloat16* b1 = (const __nv_bfloat16*)d_in[11];
  const __nv_bfloat16* w2 = (const __nv_bfloat16*)d_in[12];
  const __nv_bfloat16* b2 = (const __nv_bfloat16*)d_in[13];
  const __nv_bfloat16* gate_w = (const __nv_bfloat16*)d_in[14];
  __nv_bfloat16* out = (__nv_bfloat16*)d_out;

  static EncodeTiledFn enc = nullptr;
  static Scratch sc;
  if (!enc) {
    cudaDriverEntryPointQueryResult qr;
    cudaGetDriverEntryPoint("cuTensorMapEncodeTiled", (void**)&enc, cudaEnableDefault, &qr);
    cudaGetSymbolAddress((void**)&sc.aT, g_aT);
    cudaGetSymbolAddress((void**)&sc.xn, g_xn);
    cudaGetSymbolAddress((void**)&sc.uT, g_uT);
    cudaGetSymbolAddress((void**)&sc.gate, g_gate);
    cudaGetSymbolAddress((void**)&sc.slots, g_slots);
    cudaGetSymbolAddress((void**)&sc.slots8, g_slots8);
    cudaGetSymbolAddress((void**)&sc.flags, g_flags);
    cudaGetSymbolAddress((void**)&sc.lnflag, g_lnflag);
    sc.dbg = nullptr;
    cudaFuncSetAttribute(mlp_kernel, cudaFuncAttributeMaxDynamicSharedMemorySize, MLP_SMEM);
    cudaFuncSetAttribute(ssm_kernel, cudaFuncAttributeMaxDynamicSharedMemorySize, SSM_SMEM);
  }
  CUtensorMap tm_w1, tm_w2, tm_aT, tm_xn, tm_out;
  make_map(enc, &tm_out, d_out, D_MOD, L_SEQ, 64, 16, CU_TENSOR_MAP_SWIZZLE_128B);
  make_map(enc, &tm_xn, sc.xn, D_MOD, L_SEQ, 64, 128, CU_TENSOR_MAP_SWIZZLE_128B);
  make_map(enc, &tm_w1, (void*)w1, F_HID, D_MOD, 32, 64, CU_TENSOR_MAP_SWIZZLE_64B);
  make_map(enc, &tm_w2, (void*)w2, D_MOD, F_HID, 64, 96, CU_TENSOR_MAP_SWIZZLE_128B);
  make_map(enc, &tm_aT, sc.aT, L_SEQ, D_MOD, 64, 64, CU_TENSOR_MAP_SWIZZLE_128B);

  cudaStream_t st = cudaStreamPerThread;
  SsmArgs ar;
  ar.u = u; ar.Are = Are; ar.Aim = Aim; ar.Bre = Bre; ar.Bim = Bim; ar.Cre = Cre; ar.Cim = Cim;
  ar.logdt = logdt; ar.Dskip = Dskip; ar.gate_w = gate_w; ar.w1 = (const char*)w1; ar.w2 = (const char*)w2;
  CUtensorMap tm_x;
  make_map(enc, &tm_x, (void*)u, D_MOD, L_SEQ, 8, 256, CU_TENSOR_MAP_SWIZZLE_NONE);
  ssm_kernel<<<132, 512, SSM_SMEM, st>>>(tm_x, ar, sc);

  cudaLaunchConfig_t cfg = {};
  cfg.gridDim = dim3(128);
  cfg.blockDim = dim3(384);
  cfg.dynamicSmemBytes = MLP_SMEM;
  cfg.stream = st;
  cudaLaunchAttribute at[1];
  at[0].id = cudaLaunchAttributeProgrammaticStreamSerialization;
  at[0].val.programmaticStreamSerializationAllowed = 1;
  cfg.attrs = at;
  cfg.numAttrs = 1;
  cudaLaunchKernelEx(&cfg, mlp_kernel, tm_w1, tm_w2, tm_aT, tm_xn, tm_out, w1, w2, b1, b2, out, sc);
}
```

```cpp
#include <cuda_runtime.h>
#include <cuda_bf16.h>
#include <cuda.h>
#include <stdint.h>

#define GELU_MODE 0
#define L_SEQ 2048
#define D_MOD 576
#define F_HID 4608
#define N_ST 128

__device__ __align__(1024) __nv_bfloat16 g_aT[D_MOD * L_SEQ];
__device__ __align__(1024) __nv_bfloat16 g_xn[L_SEQ * D_MOD];
__device__ __align__(1024) uint32_t g_slots[16 * 8 * 3 * 4096];
__device__ __align__(1024) uint32_t g_slots8[16 * 8 * 4096];
__device__ uint2 g_gate[L_SEQ];
__device__ unsigned int g_flags[320];
struct Scratch {
  __nv_bfloat16* aT; __nv_bfloat16* xn; uint2* gate; uint32_t* slots; uint32_t* slots8; unsigned int* flags;
  long long* dbg;
};
#define DBG_T(i)
#define DBG_S(i)
#define DBG_H(i)
#define DBG_G(i)

__device__ __forceinline__ uint32_t smem_u32(const void* p) { return (uint32_t)__cvta_generic_to_shared(p); }
__device__ __forceinline__ void mbar_init(uint32_t bar, int cnt) {
  asm volatile("mbarrier.init.shared::cta.b64 [%0], %1;" ::"r"(bar), "r"(cnt));
}
__device__ __forceinline__ void mbar_expect_tx(uint32_t bar, uint32_t bytes) {
  asm volatile("mbarrier.arrive.expect_tx.shared::cta.b64 _, [%0], %1;" ::"r"(bar), "r"(bytes) : "memory");
}
__device__ __forceinline__ void mbar_arrive(uint32_t bar) {
  asm volatile("mbarrier.arrive.shared::cta.b64 _, [%0];" ::"r"(bar) : "memory");
}
__device__ __forceinline__ void mbar_arrive_remote(uint32_t remote_bar) {
  asm volatile("mbarrier.arrive.relaxed.cluster.shared::cluster.b64 _, [%0];" ::"r"(remote_bar) : "memory");
}
__device__ __forceinline__ void mbar_wait(uint32_t bar, uint32_t parity) {
  asm volatile(
      "{\n.reg .pred p;\n.reg .u32 n;\nmov.u32 n, 0;\n"
      "W_%=:\nmbarrier.try_wait.parity.shared::cta.b64 p, [%0], %1;\n@p bra D_%=;\n"
      "add.u32 n, n, 1;\nsetp.lt.u32 p, n, 400000;\n@p bra W_%=;\ntrap;\nD_%=:\n}"
      ::"r"(bar), "r"(parity) : "memory");
}
__device__ __forceinline__ void tma2d(uint32_t dst, const CUtensorMap* tm, int c0, int c1, uint32_t bar) {
  asm volatile("cp.async.bulk.tensor.2d.shared::cluster.global.mbarrier::complete_tx::bytes [%0], [%1, {%3, %4}], [%2];"
               ::"r"(dst), "l"(tm), "r"(bar), "r"(c0), "r"(c1) : "memory");
}
__device__ __forceinline__ void wait_flag(unsigned int* flag, unsigned int target) {
  asm volatile(
      "{\n.reg .pred p;\n.reg .u32 n, v;\nmov.u32 n, 0;\n"
      "W_%=:\nld.acquire.gpu.global.u32 v, [%0];\nsetp.ge.u32 p, v, %1;\n@p bra D_%=;\n"
      "nanosleep.u32 32;\nadd.u32 n, n, 1;\nsetp.lt.u32 p, n, 4000000;\n@p bra W_%=;\ntrap;\nD_%=:\n}"
      ::"l"(flag), "r"(target) : "memory");
}
__device__ __forceinline__ void bulk_g2s(uint32_t dst, const void* src, uint32_t bytes, uint32_t bar) {
  asm volatile("cp.async.bulk.shared::cluster.global.mbarrier::complete_tx::bytes [%0], [%1], %2, [%3];"
               ::"r"(dst), "l"(src), "r"(bytes), "r"(bar) : "memory");
}
__device__ __forceinline__ void tma3d(uint32_t dst, const CUtensorMap* tm, int c0, int c1, int c2, uint32_t bar) {
  asm volatile("cp.async.bulk.tensor.3d.shared::cluster.global.mbarrier::complete_tx::bytes [%0], [%1, {%3, %4, %5}], [%2];"
               ::"r"(dst), "l"(tm), "r"(bar), "r"(c0), "r"(c1), "r"(c2) : "memory");
}
__device__ __forceinline__ uint32_t mapa(uint32_t addr, uint32_t rank) {
  uint32_t r;
  asm("mapa.shared::cluster.u32 %0, %1, %2;" : "=r"(r) : "r"(addr), "r"(rank));
  return r;
}
__device__ __forceinline__ float4 lds128f(uint32_t addr) {
  float4 v;
  asm volatile("ld.shared.v4.f32 {%0,%1,%2,%3}, [%4];" : "=f"(v.x), "=f"(v.y), "=f"(v.z), "=f"(v.w) : "r"(addr));
  return v;
}
__device__ __forceinline__ uint32_t lds32(uint32_t addr) {
  uint32_t v;
  asm volatile("ld.shared.u32 %0, [%1];" : "=r"(v) : "r"(addr));
  return v;
}
__device__ __forceinline__ void sts128(uint32_t addr, uint32_t a, uint32_t b, uint32_t c, uint32_t d) {
  asm volatile("st.shared.v4.u32 [%0], {%1,%2,%3,%4};" ::"r"(addr), "r"(a), "r"(b), "r"(c), "r"(d) : "memory");
}
#define WG_FENCE() asm volatile("wgmma.fence.sync.aligned;" ::: "memory")
#define WG_COMMIT() asm volatile("wgmma.commit_group.sync.aligned;" ::: "memory")
template <int n> __device__ __forceinline__ void wg_wait() {
  asm volatile("wgmma.wait_group.sync.aligned %0;" ::"n"(n) : "memory");
}
__device__ __forceinline__ uint32_t pack_bf16(float lo, float hi) {
  uint32_t r;
  asm("cvt.rn.bf16x2.f32 %0, %1, %2;" : "=r"(r) : "f"(hi), "f"(lo));
  return r;
}
__device__ __forceinline__ float bf_lo(uint32_t p) { return __uint_as_float(p << 16); }
__device__ __forceinline__ float bf_hi(uint32_t p) { return __uint_as_float(p & 0xffff0000u); }
__device__ __forceinline__ float bf_round(float x) { return __bfloat162float(__float2bfloat16_rn(x)); }
__device__ __forceinline__ uint32_t bf2_add(uint32_t a, uint32_t b) {
  uint32_t r;
  asm("add.rn.bf16x2 %0, %1, %2;" : "=r"(r) : "r"(a), "r"(b));
  return r;
}
__device__ __forceinline__ uint32_t bf2_mul(uint32_t a, uint32_t b) {
  uint32_t r;
  asm("mul.rn.bf16x2 %0, %1, %2;" : "=r"(r) : "r"(a), "r"(b));
  return r;
}
__device__ __forceinline__ float tanh_fast(float x) {
  float r;
  asm("tanh.approx.f32 %0, %1;" : "=f"(r) : "f"(x));
  return r;
}
__device__ __forceinline__ float gelu_tanh(float v) {
  float p = fmaf(v * v, 0.0356774081363f, 0.7978845608029f);
  float t = tanh_fast(v * p);
  float hv = 0.5f * v;
  return fmaf(hv, t, hv);
}
__device__ __forceinline__ uint32_t bf2_fma(uint32_t a, uint32_t b, uint32_t c) {
  uint32_t r;
  asm("fma.rn.bf16x2 %0, %1, %2, %3;" : "=r"(r) : "r"(a), "r"(b), "r"(c));
  return r;
}
__device__ __forceinline__ uint32_t gelu_pack(float a0, float a1, uint32_t bias2) {
  uint32_t p = bf2_add(pack_bf16(a0, a1), bias2);
  return pack_bf16(gelu_tanh(bf_lo(p)), gelu_tanh(bf_hi(p)));
}

#define R8(a, o) "+f"(a[o]), "+f"(a[o + 1]), "+f"(a[o + 2]), "+f"(a[o + 3]), "+f"(a[o + 4]), "+f"(a[o + 5]), "+f"(a[o + 6]), "+f"(a[o + 7])
#define W8(a, o) "=f"(a[o]), "=f"(a[o + 1]), "=f"(a[o + 2]), "=f"(a[o + 3]), "=f"(a[o + 4]), "=f"(a[o + 5]), "=f"(a[o + 6]), "=f"(a[o + 7])
#define REGS48 "{%0,%1,%2,%3,%4,%5,%6,%7,%8,%9,%10,%11,%12,%13,%14,%15,%16,%17,%18,%19,%20,%21,%22,%23," \
               "%24,%25,%26,%27,%28,%29,%30,%31,%32,%33,%34,%35,%36,%37,%38,%39,%40,%41,%42,%43,%44,%45,%46,%47}"
#define REGS32 "{%0,%1,%2,%3,%4,%5,%6,%7,%8,%9,%10,%11,%12,%13,%14,%15,%16,%17,%18,%19,%20,%21,%22,%23," \
               "%24,%25,%26,%27,%28,%29,%30,%31}"
#define DESC_HI_A  "0x40000040"
#define DESC_HI_B1 "0x80000020"
#define DESC_HI_B2 "0x40000040"
template <bool ACC, int OA, int OB>
__device__ __forceinline__ void wgmma_ss_n96(float (&d)[48], uint32_t da, uint32_t db) {
  if (ACC)
    asm volatile("{\n.reg .b64 xa, xb;\n.reg .b32 la, lb;\nadd.u32 la, %48, %50;\nadd.u32 lb, %49, %51;\n"
                 "mov.b64 xa, {la, " DESC_HI_A "};\nmov.b64 xb, {lb, " DESC_HI_B1 "};\n"
                 "wgmma.mma_async.sync.aligned.m64n96k16.f32.bf16.bf16 " REGS48 ", xa, xb, 1, 1, 1, 0, 1;\n}\n"
                 : R8(d, 0), R8(d, 8), R8(d, 16), R8(d, 24), R8(d, 32), R8(d, 40) : "r"(da), "r"(db), "n"(OA), "n"(OB));
  else
    asm volatile("{\n.reg .b64 xa, xb;\n.reg .b32 la, lb;\nadd.u32 la, %48, %50;\nadd.u32 lb, %49, %51;\n"
                 "mov.b64 xa, {la, " DESC_HI_A "};\nmov.b64 xb, {lb, " DESC_HI_B1 "};\n"
                 "wgmma.mma_async.sync.aligned.m64n96k16.f32.bf16.bf16 " REGS48 ", xa, xb, 0, 1, 1, 0, 1;\n}\n"
                 : W8(d, 0), W8(d, 8), W8(d, 16), W8(d, 24), W8(d, 32), W8(d, 40) : "r"(da), "r"(db), "n"(OA), "n"(OB));
}
template <bool ACC, int OB>
__device__ __forceinline__ void wgmma_rs_n64(float (&d)[32], uint32_t a0, uint32_t a1, uint32_t a2, uint32_t a3, uint32_t db) {
  if (ACC)
    asm volatile("{\n.reg .b64 xb;\n.reg .b32 lb;\nadd.u32 lb, %36, %37;\nmov.b64 xb, {lb, " DESC_HI_B2 "};\n"
                 "wgmma.mma_async.sync.aligned.m64n64k16.f32.bf16.bf16 " REGS32 ", {%32,%33,%34,%35}, xb, 1, 1, 1, 1;\n}\n"
                 : R8(d, 0), R8(d, 8), R8(d, 16), R8(d, 24) : "r"(a0), "r"(a1), "r"(a2), "r"(a3), "r"(db), "n"(OB));
  else
    asm volatile("{\n.reg .b64 xb;\n.reg .b32 lb;\nadd.u32 lb, %36, %37;\nmov.b64 xb, {lb, " DESC_HI_B2 "};\n"
                 "wgmma.mma_async.sync.aligned.m64n64k16.f32.bf16.bf16 " REGS32 ", {%32,%33,%34,%35}, xb, 0, 1, 1, 1;\n}\n"
                 : W8(d, 0), W8(d, 8), W8(d, 16), W8(d, 24) : "r"(a0), "r"(a1), "r"(a2), "r"(a3), "r"(db), "n"(OB));
}
template <int N> __device__ __forceinline__ void fence_regs(float (&d)[N]) {
#pragma unroll
  for (int i = 0; i < N; i++) asm volatile("" : "+f"(d[i])::"memory");
}

constexpr int XS_BYTES = 9 * 16384;
constexpr int STAGE_BYTES = 12288;
constexpr int OFF_ST = XS_BYTES;
constexpr int OFF_B1 = OFF_ST + 6 * STAGE_BYTES;
constexpr int OFF_B2 = OFF_B1 + 1152;
constexpr int OFF_BAR = OFF_B2 + 1152;
constexpr int B_FULL = 0, B_X = 48  , B_RB = 120  , B_OWN = 152, B_FIN = 160, B_A8 = 168,
              B_EMPTY = 176  , B_TS = 224  , B_TS8 = 256, B_TR = 264  , B_P1L = 288, B_P1R = 296, B_U = 304,
              NBARS = 39;
constexpr int OFF_A8 = OFF_BAR + 512;
constexpr int OFF_ARGS = OFF_A8 + 2048;
constexpr int SMEM_BYTES = OFF_ARGS + 256 + 1024;
constexpr int OFF_STG = 65536, OFF_C8 = 131072;
constexpr int E_UA = 0, E_UB = 3616, E_W3A = 7232, E_W3B = 10848, E_W5 = 14464, E_W9 = 17568, E_TAP = 19680, E_SIZE = 23392;
constexpr int L_W7 = 4752, L_KB = 6832, L_Y = 6848, L_YB = 8304, L_SIZE = 28656;
constexpr int L_CONST = L_Y, L_KC = L_Y + 10240;
constexpr int TP_0 = 0, TP_W3A = 580, TP_UA = 716, TP_UB = 852, TP_W3B = 988, TP_W5 = 1248, TP_W9 = 1448, TP_W7 = 1648,
              TP_COPY = 1856;
__device__ __forceinline__ int e_off(int ch) { return ch == 0 ? 0 : OFF_ST + (ch - 1) * E_SIZE; }
__device__ __forceinline__ int l_off(int ch) { return 32768 + ch * L_SIZE; }
__device__ __forceinline__ int xg_off(int box) { return box < 4 ? OFF_ST + box * 4096 : 170880 + (box - 4) * 4096; }

__device__ __forceinline__ void ln_load(const __nv_bfloat16* __restrict__ x, const __nv_bfloat16* __restrict__ gate_w,
                                        int row, int lane, uint32_t (&w)[9], uint32_t (&gw)[9]) {
  const uint32_t* xr = reinterpret_cast<const uint32_t*>(x + (size_t)row * D_MOD) + lane;
  const uint32_t* gwp = reinterpret_cast<const uint32_t*>(gate_w) + lane;
#pragma unroll
  for (int j = 0; j < 9; j++) {
    asm volatile("ld.global.nc.u32 %0, [%1];" : "=r"(w[j]) : "l"(xr + j * 32));
    asm volatile("ld.global.nc.u32 %0, [%1];" : "=r"(gw[j]) : "l"(gwp + j * 32));
  }
}
__device__ __forceinline__ void ln_row(int row, int lane, const Scratch& sc, const uint32_t (&w)[9], const uint32_t (&gw)[9]) {
  float s = 0.f, gsum = 0.f;
#pragma unroll
  for (int j = 0; j < 9; j++) {
    uint32_t pr2 = bf2_mul(w[j], gw[j]);
    s += bf_lo(w[j]) + bf_hi(w[j]);
    gsum += bf_lo(pr2) + bf_hi(pr2);
  }
#pragma unroll
  for (int o = 1; o < 32; o <<= 1) { s += __shfl_xor_sync(~0u, s, o); gsum += __shfl_xor_sync(~0u, gsum, o); }
  const float mean = s * (1.0f / 576.0f);
  float vs = 0.f;
#pragma unroll
  for (int j = 0; j < 9; j++) {
    float d0 = bf_lo(w[j]) - mean, d1 = bf_hi(w[j]) - mean;
    vs = fmaf(d0, d0, vs); vs = fmaf(d1, d1, vs);
  }
#pragma unroll
  for (int o = 1; o < 32; o <<= 1) vs += __shfl_xor_sync(~0u, vs, o);
  const float mb = bf_round(mean);
  const float vb = bf_round(vs * (1.0f / 576.0f));
  const float rinv = __frcp_rn(bf_round(__fsqrt_rn(bf_round(vb + 1e-5f))));
  const uint32_t nm2 = pack_bf16(-mb, -mb);
  uint32_t* dst = reinterpret_cast<uint32_t*>(sc.xn + (size_t)row * D_MOD) + lane;
#pragma unroll
  for (int j = 0; j < 9; j++) {
    uint32_t dd = bf2_add(w[j], nm2);
    dst[j * 32] = pack_bf16(bf_lo(dd) * rinv, bf_hi(dd) * rinv);
  }
  if (lane == 0) {
    float gv = bf_round(__fdividef(1.0f, 1.0f + __expf(-bf_round(gsum))));
    float og = bf_round(1.0f - gv);
    sc.gate[row] = make_uint2(pack_bf16(gv, gv), pack_bf16(og, og));
  }
}
__device__ __forceinline__ void mma_bf16(float (&d)[4], uint32_t a0, uint32_t a1, uint32_t a2, uint32_t a3, uint32_t b0, uint32_t b1) {
  asm("mma.sync.aligned.m16n8k16.row.col.f32.bf16.bf16.f32 {%0,%1,%2,%3}, {%4,%5,%6,%7}, {%8,%9}, {%0,%1,%2,%3};"
      : "+f"(d[0]), "+f"(d[1]), "+f"(d[2]), "+f"(d[3]) : "r"(a0), "r"(a1), "r"(a2), "r"(a3), "r"(b0), "r"(b1));
}
__device__ __forceinline__ void mma_tf32(float (&d)[4], float a0, float a1, float a2, float a3, float b0, float b1) {
  asm("mma.sync.aligned.m16n8k8.row.col.f32.tf32.tf32.f32 {%0,%1,%2,%3}, {%4,%5,%6,%7}, {%8,%9}, {%0,%1,%2,%3};"
      : "+f"(d[0]), "+f"(d[1]), "+f"(d[2]), "+f"(d[3])
      : "r"(__float_as_uint(a0)), "r"(__float_as_uint(a1)), "r"(__float_as_uint(a2)), "r"(__float_as_uint(a3)),
        "r"(__float_as_uint(b0)), "r"(__float_as_uint(b1)));
}
__device__ __forceinline__ float2 cexp_l(float al, float th, float l) {
  float mg;
  asm("ex2.approx.ftz.f32 %0, %1;" : "=f"(mg) : "f"(al * l));
  const float tr = th * l;
  return make_float2(mg * __cosf(tr), mg * __sinf(tr));
}
__device__ __forceinline__ float2 cmul(float2 a, float2 b) {
  return make_float2(fmaf(a.x, b.x, -a.y * b.y), fmaf(a.x, b.y, a.y * b.x));
}
__device__ __forceinline__ float2 cmulc(float2 a, float2 b) {
  return make_float2(fmaf(a.x, b.x, -a.y * b.y), fmaf(-a.x, b.y, -a.y * b.x));
}
__device__ __forceinline__ float2 csq(float2 a) { return make_float2(fmaf(a.x, a.x, -a.y * a.y), 2.0f * a.x * a.y); }
#define SM_U32(p) (*reinterpret_cast<uint32_t*>(p))
#define SM_F32(p) (*reinterpret_cast<float*>(p))
#define SM_U16(p) (*reinterpret_cast<unsigned short*>(p))
#define SM_U2(p) (*reinterpret_cast<uint2*>(p))
#define SM_F2(p) (*reinterpret_cast<float2*>(p))
#define SM_U4(p) (*reinterpret_cast<uint4*>(p))
#define SM_F4(p) (*reinterpret_cast<float4*>(p))
template <int OFF, int TAG>
__device__ __forceinline__ uint32_t lds_free(uint32_t base) {
  uint32_t v;
  asm volatile("ld.volatile.shared.u32 %0, [%1+%2]; // %3" : "=r"(v) : "r"(base), "n"(OFF), "n"(TAG));
  return v;
}
template <int K, int OFF>
__device__ __forceinline__ void load_tquad(uint32_t (&q)[4], uint32_t tp) {
  q[0] = lds_free<OFF - 32 * K, 0>(tp);
  q[1] = lds_free<OFF - 32 * K - 16, 1>(tp);
  q[2] = lds_free<OFF - 32 * K + 16, 2>(tp);
  q[3] = lds_free<OFF - 32 * K, 3>(tp);
}
template <int K0, int K1, int OFF>
__device__ __forceinline__ void load_tquads(uint32_t (&q)[K1 - K0][4], uint32_t tp) {
  if constexpr (K1 > K0) {
    load_tquad<K1 - 1, OFF>(q[K1 - K0 - 1], tp);
    if constexpr (K1 - 1 > K0) load_tquads<K0, K1 - 1, OFF>(reinterpret_cast<uint32_t (&)[K1 - K0 - 1][4]>(q), tp);
  }
}
__device__ __forceinline__ void ldsm4_free(uint32_t (&r)[4], uint32_t addr) {
  asm("ldmatrix.sync.aligned.m8n8.x4.shared.b16 {%0,%1,%2,%3}, [%4];"
      : "=r"(r[0]), "=r"(r[1]), "=r"(r[2]), "=r"(r[3]) : "r"(addr));
}
__device__ __forceinline__ void ldsm4t_free(uint32_t (&r)[4], uint32_t addr) {
  asm("ldmatrix.sync.aligned.m8n8.x4.trans.shared.b16 {%0,%1,%2,%3}, [%4];"
      : "=r"(r[0]), "=r"(r[1]), "=r"(r[2]), "=r"(r[3]) : "r"(addr));
}
__device__ __forceinline__ uint32_t ldg_u16(const __nv_bfloat16* p) {
  unsigned short v;
  asm volatile("ld.global.nc.u16 %0, [%1];" : "=h"(v) : "l"(p));
  return v;
}
__device__ __forceinline__ void ldsm4t(uint32_t (&r)[4], uint32_t addr) {
  asm volatile("ldmatrix.sync.aligned.m8n8.x4.trans.shared.b16 {%0,%1,%2,%3}, [%4];"
               : "=r"(r[0]), "=r"(r[1]), "=r"(r[2]), "=r"(r[3]) : "r"(addr) : "memory");
}
template <int I0, int I1, int K0, int K1, int JMIN, int RB, int TOFF>
__device__ __forceinline__ void band(float (&acc)[I1 - I0][4], uint32_t tp, uint32_t sa, uint32_t za, int lane) {
  uint32_t tq[K1 - K0][4];
  load_tquads<K0, K1, TOFF>(tq, tp);
  constexpr int JL = (I0 - K1 + 1 > JMIN) ? I0 - K1 + 1 : JMIN, JH = I1 - 1 - K0;
  constexpr int JP = (JL >= 0) ? (JL & ~1) : -2;
#pragma unroll
  for (int J2 = JP; J2 <= JH; J2 += 2) {
    uint32_t b[4];
    ldsm4t_free(b, (J2 < 0 && lane < 31) ? za : sa + J2 * 16 * RB);
#pragma unroll
    for (int hf = 0; hf < 2; hf++) {
      const int J = J2 + hf;
#pragma unroll
      for (int k = K0; k < K1; k++) {
        const int I = J + k;
        if (J >= JL && J <= JH && I >= I0 && I < I1)
          mma_bf16(acc[I - I0], tq[k - K0][0], tq[k - K0][1], tq[k - K0][2], tq[k - K0][3], b[2 * hf], b[2 * hf + 1]);
      }
    }
  }
}
template <int I0, int I1>
__device__ __forceinline__ void p8_tiles(uint32_t ea, uint32_t za, char* lb, uint32_t tp, int lane) {
  float acc[I1 - I0][4];
#pragma unroll
  for (int i = 0; i < I1 - I0; i++) { acc[i][0] = acc[i][1] = acc[i][2] = acc[i][3] = 0.f; }
  const uint32_t sa = ea + 32 + lane * 16;
  band<I0, I1, 2, 5, -1, 16, TP_W3A + 160>(acc, tp, sa + E_W3A, za, lane);
  band<I0, I1, 2, 5, 0, 16, TP_UA + 160>(acc, tp, sa + E_UA, za, lane);
  band<I0, I1, 2, 5, 0, 16, TP_UB + 160>(acc, tp, sa + E_UB, za, lane);
  band<I0, I1, 2, 9, 0, 16, TP_W3B + 288>(acc, tp, sa + E_W3B, za, lane);
  band<I0, I1, 4, 9, -1, 16, TP_W5 + 288>(acc, tp, sa + E_W5, za, lane);
  char* a = lb + L_Y + L_YB + 4 * (8 * (lane >> 2) + 2 * (lane & 3));
#pragma unroll
  for (int I = I0; I < I1; I++) {
    SM_F2(a + 4 * (128 * I + 4 * (I >> 1))) = make_float2(acc[I - I0][0], acc[I - I0][1]);
    SM_F2(a + 4 * (128 * I + 4 * (I >> 1)) + 256) = make_float2(acc[I - I0][2], acc[I - I0][3]);
  }
}

struct MlpCtx {
  uint32_t bars;
  uint32_t dA, dB;
  int lane;
};
__device__ __forceinline__ void stage_release(const MlpCtx& c, int slot) {
  if (c.lane == 0) mbar_arrive(c.bars + B_EMPTY + 8 * slot);
}
template <int P>
__device__ __forceinline__ void gelu_part(uint32_t baddr, float (&acc)[48]) {
  asm volatile("" : R8(acc, P * 8)::"memory");
  uint32_t b0 = lds32(baddr + P * 32), b1 = lds32(baddr + P * 32 + 16);
  uint32_t r0 = gelu_pack(acc[P * 8 + 0], acc[P * 8 + 1], b0);
  uint32_t r1 = gelu_pack(acc[P * 8 + 2], acc[P * 8 + 3], b0);
  uint32_t r2 = gelu_pack(acc[P * 8 + 4], acc[P * 8 + 5], b1);
  uint32_t r3 = gelu_pack(acc[P * 8 + 6], acc[P * 8 + 7], b1);
  acc[P * 8 + 0] = __uint_as_float(r0);
  acc[P * 8 + 1] = __uint_as_float(r1);
  acc[P * 8 + 2] = __uint_as_float(r2);
  acc[P * 8 + 3] = __uint_as_float(r3);
}
__device__ __forceinline__ void h_push(uint32_t (&h)[144], float (&acc)[48]) {
  asm volatile("" : R8(acc, 0)::"memory");
#pragma unroll
  for (int i = 0; i < 96; i++) h[i] = h[i + 24];
#pragma unroll
  for (int i = 0; i < 24; i++) h[96 + i] = __float_as_uint(acc[(i >> 2) * 8 + (i & 3)]);
}
template <int SB, int I>
__device__ __forceinline__ void p1_mma(const MlpCtx& c, float (&cur)[48]) {
  constexpr int S = SB % 9;
  wgmma_ss_n96<(S | I) != 0, ((S * 16384 + I * 32) >> 4),
               (4096 >> 4 << 16) + (((SB % 6) * STAGE_BYTES + I * 1024) >> 4)>(cur, c.dA, c.dB);
}
template <int SB>
__device__ __forceinline__ void p1_stage(const MlpCtx& c, int j, uint32_t baddr, float (&cur)[48], float (&prev)[48],
                                         uint32_t (&h)[144]) {
  constexpr int S = SB % 9;
  if (SB < 9) mbar_wait(c.bars + B_X + 8 * S, 0);
  mbar_wait(c.bars + B_FULL + 8 * (SB % 6), ((SB / 6) + j) & 1);
  WG_FENCE();
  p1_mma<SB, 0>(c, cur); p1_mma<SB, 1>(c, cur); p1_mma<SB, 2>(c, cur); p1_mma<SB, 3>(c, cur);
  WG_COMMIT();
  if (S >= 1 && S <= 6) gelu_part<(S >= 1 && S <= 6) ? S - 1 : 0>(baddr, prev);
  if (S == 7) h_push(h, prev);
  wg_wait<1>();
  if (SB > 0 || j > 0) stage_release(c, (SB + 5) % 6);
  if (S == 0) fence_regs(prev);
}
template <int SB0>
__device__ __forceinline__ void p1_chunk(const MlpCtx& c, int j, uint32_t baddr, float (&cur)[48], float (&prev)[48],
                                         uint32_t (&h)[144]) {
  p1_stage<SB0 + 0>(c, j, baddr, cur, prev, h); p1_stage<SB0 + 1>(c, j, baddr, cur, prev, h);
  p1_stage<SB0 + 2>(c, j, baddr, cur, prev, h); p1_stage<SB0 + 3>(c, j, baddr, cur, prev, h);
  p1_stage<SB0 + 4>(c, j, baddr, cur, prev, h); p1_stage<SB0 + 5>(c, j, baddr, cur, prev, h);
  p1_stage<SB0 + 6>(c, j, baddr, cur, prev, h); p1_stage<SB0 + 7>(c, j, baddr, cur, prev, h);
  p1_stage<SB0 + 8>(c, j, baddr, cur, prev, h);
}
template <int S, int I>
__device__ __forceinline__ void p2_one(const MlpCtx& c, float (&cur)[32], uint32_t (&h)[144]) {
  constexpr int kk = 6 * S + I;
  wgmma_rs_n64<(S | I) != 0, ((S * STAGE_BYTES + I * 2048) >> 4)>(cur, h[4 * kk], h[4 * kk + 1], h[4 * kk + 2], h[4 * kk + 3], c.dB);
}
template <int S>
__device__ __forceinline__ void p2_mma(const MlpCtx& c, uint32_t parity, float (&cur)[32], uint32_t (&h)[144]) {
  mbar_wait(c.bars + B_FULL + 8 * S, parity);
  WG_FENCE();
  p2_one<S, 0>(c, cur, h); p2_one<S, 1>(c, cur, h); p2_one<S, 2>(c, cur, h);
  p2_one<S, 3>(c, cur, h); p2_one<S, 4>(c, cur, h); p2_one<S, 5>(c, cur, h);
  WG_COMMIT();
}
__device__ __forceinline__ int chunk_of(int pos, int pr, int rank) {
  const int off = (int)(0x03231201ull >> (4 * pos)) & 3;
  const int mine = (0x168 >> pos) & 1;
  return pos == 1 ? 8 : 2 * ((pr + off) & 3) + (mine ? rank : rank ^ 1);
}
__device__ __forceinline__ void bulk_s2peer(uint32_t rdst, uint32_t src, uint32_t bytes, uint32_t rbar) {
  asm volatile("cp.async.bulk.shared::cluster.shared::cta.mbarrier::complete_tx::bytes [%0], [%1], %2, [%3];"
               ::"r"(rdst), "r"(src), "r"(bytes), "r"(rbar) : "memory");
}
__device__ __forceinline__ void bulk_s2g_release(void* gdst, uint32_t src, uint32_t bytes) {
  asm volatile("cp.async.bulk.global.shared::cta.bulk_group [%0], [%1], %2;\n"
               "cp.async.bulk.commit_group;\ncp.async.bulk.wait_group 0;\nfence.acq_rel.gpu;"
               ::"l"(gdst), "r"(src), "r"(bytes) : "memory");
}
struct Args {
  const __nv_bfloat16 *u, *Are, *Aim, *Bre, *Bim, *Cre, *Cim, *logdt, *Dskip, *gate_w, *w1, *w2, *b1, *b2;
  __nv_bfloat16* out;
};

struct Maps { const CUtensorMap *x, *w1, *xn; };
__device__ __forceinline__ void load_params(uint32_t (&v)[8], const Args& ar, int d, int n) {
  const int idx = d * N_ST + n;
  v[0] = ldg_u16(ar.Are + idx); v[1] = ldg_u16(ar.Aim + idx); v[2] = ldg_u16(ar.Bre + idx); v[3] = ldg_u16(ar.Bim + idx);
  v[4] = ldg_u16(ar.Cre + idx); v[5] = ldg_u16(ar.Cim + idx); v[6] = ldg_u16(ar.logdt + d); v[7] = ldg_u16(ar.Dskip + d);
}
__device__ __forceinline__ uint4 pack_params(uint32_t (&v)[8]) {
  asm volatile("" : "+r"(v[0]), "+r"(v[1]), "+r"(v[2]), "+r"(v[3]), "+r"(v[4]), "+r"(v[5]), "+r"(v[6]), "+r"(v[7])::"memory");
  return make_uint4(v[0] | (v[1] << 16), v[2] | (v[3] << 16), v[4] | (v[5] << 16), v[6] | (v[7] << 16));
}
__device__ __noinline__ void ssm_pass(const Maps tm, char* sm, const int d0, const int pass
) {
  const Args& ar = *reinterpret_cast<const Args*>(sm + OFF_ARGS);
  const Scratch& sc = *reinterpret_cast<const Scratch*>(sm + OFF_ARGS + 128);
  const uint32_t sb = smem_u32(sm), bars = sb + OFF_BAR;
  const int tid = threadIdx.x, lane = tid & 31;
  const int warp = __shfl_sync(0xffffffffu, tid >> 5, 0);
  const int bid = blockIdx.x, m = bid >> 3, f = bid & 7;
  const int g = lane >> 2, cc = lane & 3;
  const int ch = warp >> 2, n = tid & 127;
  char* eb = sm + e_off(ch);
  char* lb = sm + l_off(ch);
#define CH_SYNC() asm volatile("bar.sync %0, 128;" ::"r"(ch + 1) : "memory")
  {
    uint32_t praw[8];
    if (pass == 0) load_params(praw, ar, d0 + ch, n);
    if (pass == 0 && lane == 0 && (warp & 1) == 0) {
      mbar_expect_tx(bars + B_U, 4096);
      tma2d(sb + xg_off(warp >> 1), tm.x, d0 & ~7, (warp >> 1) * 256, bars + B_U);
    }
    if (pass == 0) {
      const uint4 z = make_uint4(0, 0, 0, 0);
      SM_U4(eb + E_TAP + n * 16) = z;
      if (n < 104) SM_U4(eb + E_TAP + 2048 + n * 16) = z;
      else if (n == 104) SM_U4(eb + E_W9) = z;
      if (n < 33) SM_U4(lb + n * 16) = z;
    }
    const uint4 pv = pass == 0 ? pack_params(praw) : SM_U4(sm + tid * 16);
    const float are = bf_lo(pv.x), aim = bf_hi(pv.x), bre = bf_lo(pv.y), bim = bf_hi(pv.y);
    const float cre = bf_lo(pv.z), cim = bf_hi(pv.z), ldt = bf_lo(pv.w), dsk = bf_hi(pv.w);
    const float dt = bf_round(expf(ldt));
    const float al = (dt * are) * 1.4426950408889634f, th = dt * aim;
    const float2 c0 = cmul(make_float2(cre, cim), make_float2(dt * bre, dt * bim));
    const float2 e64 = cexp_l(al, th, 64.f), e128 = csq(e64), e256 = cexp_l(al, th, 256.f), e512 = csq(e256);
    const float2 k128 = cmul(c0, e128), k256 = cmul(c0, e256), k384 = cmul(k256, e128);
    const float2 k512 = cmul(c0, e512), k516 = cmul(k512, cexp_l(al, th, 4.f));
    const float2 e1024 = cexp_l(al, th, 1024.f), k1024 = cmul(c0, e1024);
    float k2048 = fmaf(k1024.x, e1024.x, -k1024.y * e1024.y);
    char* ca = lb + L_CONST + n * 80;
    SM_F4(ca) = make_float4(al, th, e64.x, e64.y);
    SM_F4(ca + 16) = make_float4(c0.x, c0.y, k128.x, k128.y);
    SM_F4(ca + 32) = make_float4(k256.x, k256.y, k384.x, k384.y);
    SM_F4(ca + 48) = make_float4(k512.x, k512.y, k516.x, k516.y);
    SM_F2(ca + 64) = k1024;
#pragma unroll
    for (int o = 16; o > 0; o >>= 1) k2048 += __shfl_xor_sync(~0u, k2048, o);
    if (lane == 0) SM_F32(lb + L_KC + (warp & 3) * 2576 + 2560) = k2048;
    if (n == 0) SM_F32(lb + L_KB + 8) = dsk;
    __syncwarp();
    DBG_S(0);
    float kd[5][4];
#pragma unroll
    for (int t = 0; t < 5; t++) { kd[t][0] = kd[t][1] = kd[t][2] = kd[t][3] = 0.f; }
    const float l1 = (float)g, l128 = (float)(128 * g);
    const char* cr = lb + L_CONST + ((warp & 3) * 32 + cc) * 80;
    const int o2 = 32 + (g >> 2) * 8, o3 = 48 + (g & 1) * 8, s2 = ((g & 3) << 2) | cc, s3 = ((g >> 1) << 2) | cc;
#pragma unroll 2
    for (int st = 0; st < 8; st++, cr += 320) {
      const float4 q0 = *(const float4*)cr, q1 = *(const float4*)(cr + 16);
      const float2 q2 = *(const float2*)(cr + o2), q3 = *(const float2*)(cr + o3), q4 = *(const float2*)(cr + 64);
      const float2 p1 = cexp_l(q0.x, q0.y, l1), p128 = cexp_l(q0.x, q0.y, l128);
      const float2 p2 = csq(p1), p8 = csq(csq(p2));
      const float2 a1 = cmul(p8, make_float2(q0.z, q0.w));
      float2 x = cmulc(make_float2(q1.x, q1.y), p1);
      mma_tf32(kd[0], p8.x, a1.x, p8.y, a1.y, x.x, x.y);
      x = cmulc(make_float2(q1.z, q1.w), p1);
      mma_tf32(kd[1], p8.x, a1.x, p8.y, a1.y, x.x, x.y);
      x = cmulc(q2, make_float2(__shfl_sync(~0u, p2.x, s2), __shfl_sync(~0u, p2.y, s2)));
      mma_tf32(kd[2], p8.x, a1.x, p8.y, a1.y, x.x, x.y);
      x = cmulc(q3, make_float2(__shfl_sync(~0u, p128.x, s3), __shfl_sync(~0u, p128.y, s3)));
      mma_tf32(kd[3], p8.x, a1.x, p8.y, a1.y, x.x, x.y);
      x = cmulc(q4, p128);
      mma_tf32(kd[4], p8.x, a1.x, p8.y, a1.y, x.x, x.y);
    }
    char* kc = lb + L_KC + (warp & 3) * 2576;
#pragma unroll
    for (int e = 0; e < 2; e++) {
      const int row = g + e * 8;
      SM_F2(kc + 4 * (8 * row + 2 * cc)) = make_float2(kd[0][2 * e], kd[0][2 * e + 1]);
      SM_F2(kc + 4 * (128 + 8 * row + 2 * cc)) = make_float2(kd[1][2 * e], kd[1][2 * e + 1]);
      SM_F2(kc + 4 * (256 + 64 * (cc >> 1) + 4 * row + 2 * (cc & 1))) = make_float2(kd[2][2 * e], kd[2][2 * e + 1]);
      SM_F2(kc + 4 * (384 + 32 * cc + 2 * row)) = make_float2(kd[3][2 * e], kd[3][2 * e + 1]);
      SM_F32(kc + 4 * (512 + 32 * cc + row)) = kd[4][2 * e];
      SM_F32(kc + 4 * (528 + 32 * cc + row)) = kd[4][2 * e + 1];
    }
  }
  DBG_S(1);
  uint32_t lw[9], lg[9];
  ln_load(ar.u, ar.gate_w, (bid & 127) * 16 + warp, lane, lw, lg);
  CH_SYNC();
  {
    const char* kc = lb + L_KC;
    auto kq = [&](int idx) {
      const char* q = kc + 4 * idx;
      return (*(const float*)q + *(const float*)(q + 2576)) + (*(const float*)(q + 5152) + *(const float*)(q + 7728));
    };
#pragma unroll
    for (int it = 0; it < 5; it++) {
      const int idx = n + 128 * it;
      float t = kq(idx);
      if ((it == 1 || it == 2) && n == 127) t -= kq(idx + 1);
      if (it == 4 && n == 0) { SM_F2(lb + L_KB) = make_float2(t, kq(640)); t = 0.f; }
      int off;
      if (it < 2) off = TP_0 + 2 * (272 - idx);
      else if (it == 2) {
        const int sel = n & 3, mu = 32 + (n >> 2);
        off = sel == 2 ? TP_W3B + 2 * (144 - mu) : (sel == 0 ? TP_W3A : sel == 1 ? TP_UA : TP_UB) + 2 * (80 - mu);
      } else if (it == 3) off = ((n & 1) ? TP_W3B : TP_W5) + 2 * (80 - (n >> 1));
      else off = ((n & 1) ? TP_W7 : TP_W9) + 2 * (80 - (n >> 1));
      const unsigned short hv = pack_bf16(t, 0.f);
      SM_U16(eb + E_TAP + off) = hv;
      SM_U16(eb + E_TAP + TP_COPY + off + 2) = hv;
    }
  }
  DBG_S(2);
  if (bid < 128) ln_row(bid * 16 + warp, lane, sc, lw, lg);
  DBG_S(3);
  mbar_wait(bars + B_U, pass & 1);
  {
    const uint32_t src = sb + xg_off(warp >> 1) + ((warp & 1) * 128 + lane) * 16;
    const int mych = g - (d0 & 4);
    char* dst = sm + l_off(mych) + ((warp >> 1) + 1) * 528 + (warp & 1) * 256 + cc * 4;
#pragma unroll
    for (int i = 0; i < 4; i++) {
      uint32_t r[4];
      ldsm4t(r, src + i * 512);
      if (mych >= 0 && mych < 4) {
#pragma unroll
        for (int k = 0; k < 4; k++) SM_U32(dst + i * 64 + k * 16) = r[k];
      }
    }
  }
  __syncthreads();
  DBG_S(4);
  if (bid < 128) {
    if (tid == 480) {
      asm volatile("fence.acq_rel.gpu;" ::: "memory");
      atomicAdd(&sc.flags[256 + m], 1u);
    } else if (tid == 0) {
      asm volatile("cp.async.bulk.prefetch.L2.global [%0], %1;" ::"l"(ar.w1 + (size_t)bid * 20736), "r"(41472) : "memory");
      asm volatile("cp.async.bulk.prefetch.L2.global [%0], %1;" ::"l"(ar.w2 + (size_t)bid * 20736), "r"(41472) : "memory");
    }
  }
#pragma unroll 1
  for (int i = n - 1; i < 224; i += 128) {
    const char* ur = lb + ((i >> 5) + 1) * 528 + (i & 31) * 16;
    const uint4 w0 = *(const uint4*)(ur - ((i & 31) ? 16 : 32) + (i < 0 ? 16 : 0)), w1 = *(const uint4*)ur,
                w2 = *(const uint4*)(ur + ((i & 31) == 31 ? 32 : 16));
    const uint32_t wv[12] = {w0.x, w0.y, w0.z, w0.w, w1.x, w1.y, w1.z, w1.w, w2.x, w2.y, w2.z, w2.w};
    char* o = eb + 32 + 16 * i;
    SM_U4(o + E_UA) = make_uint4(wv[3], wv[4], wv[5], wv[6]);
    SM_U4(o + E_UB) = make_uint4(wv[1], wv[2], wv[3], wv[4]);
    float v[22], wa[16];
#pragma unroll
    for (int k = 1; k < 11; k++) { v[2 * k] = bf_lo(wv[k]); v[2 * k + 1] = bf_hi(wv[k]); }
#pragma unroll
    for (int k = 4; k < 16; k++) wa[k] = (v[k - 1] + v[k]) + v[k + 1];
    SM_U4(o + E_W3A) = make_uint4(pack_bf16(wa[8], wa[9]), pack_bf16(wa[10], wa[11]), pack_bf16(wa[12], wa[13]), pack_bf16(wa[14], wa[15]));
    SM_U4(o + E_W3B) = make_uint4(pack_bf16(wa[4], wa[5]), pack_bf16(wa[6], wa[7]), pack_bf16(wa[8], wa[9]), pack_bf16(wa[10], wa[11]));
    if (i < 192) {
#pragma unroll
      for (int k = 8; k < 16; k++) wa[k] += v[k - 2] + v[k + 2];
      SM_U4(o + E_W5) = make_uint4(pack_bf16(wa[8], wa[9]), pack_bf16(wa[10], wa[11]), pack_bf16(wa[12], wa[13]), pack_bf16(wa[14], wa[15]));
      if (i < 128) {
#pragma unroll
        for (int k = 8; k < 16; k++) wa[k] += v[k - 3] + v[k + 3];
        SM_U4(lb + L_W7 + 32 + 16 * i) =
            make_uint4(pack_bf16(wa[8], wa[9]), pack_bf16(wa[10], wa[11]), pack_bf16(wa[12], wa[13]), pack_bf16(wa[14], wa[15]));
#pragma unroll
        for (int k = 8; k < 16; k++) wa[k] += v[k - 4] + v[k + 4];
        SM_U4(o + E_W9) = make_uint4(pack_bf16(wa[8], wa[9]), pack_bf16(wa[10], wa[11]), pack_bf16(wa[12], wa[13]), pack_bf16(wa[14], wa[15]));
      }
    }
  }
  CH_SYNC();
  DBG_S(5);
  {
    const int role = (warp + ch) & 3;
    uint32_t ea = smem_u32(eb), za = smem_u32(lb);
    asm volatile("" : "+r"(ea), "+r"(za)::"memory");
    const uint32_t tp = ea + E_TAP + ((g & 1) ? TP_COPY + 2 : 0) - 2 * (g - 2 * cc);
    if (role < 2) {
      uint32_t ta[17][4];
      load_tquads<0, 17, TP_0 + 544>(ta, tp);
      float acc[8][4];
#pragma unroll
      for (int i = 0; i < 8; i++) { acc[i][0] = acc[i][1] = acc[i][2] = acc[i][3] = 0.f; }
      const uint32_t bpos = za + ((lane & 7) + 1) * 528 + role * 256 + (lane >> 3) * 16;
      const uint32_t bmid = role ? bpos : bpos - 16;
#pragma unroll
      for (int j2 = -16; j2 < 8; j2 += 2) {
        uint32_t b[4];
        ldsm4_free(b, (j2 < -8 ? bpos - 16 : j2 < 0 ? bmid : bpos) + 32 * j2);
#pragma unroll
        for (int hf = 0; hf < 2; hf++) {
#pragma unroll
          for (int i = 0; i < 8; i++) {
            const int k = i - j2 - hf;
            if (k >= 0 && k <= 16) mma_bf16(acc[i], ta[k][0], ta[k][1], ta[k][2], ta[k][3], b[2 * hf], b[2 * hf + 1]);
          }
        }
      }
      char* ya = lb + L_Y + 4 * (520 * cc + 128 * role + g);
#pragma unroll
      for (int i = 0; i < 8; i++) {
        SM_F32(ya + 64 * i) = acc[i][0]; SM_F32(ya + 64 * i + 1040) = acc[i][1];
        SM_F32(ya + 64 * i + 32) = acc[i][2]; SM_F32(ya + 64 * i + 1072) = acc[i][3];
      }
    } else if (role == 2) {
      p8_tiles<1, 11>(ea, za, lb, tp, lane);
    } else {
      p8_tiles<11, 16>(ea, za, lb, tp, lane);
#pragma unroll 1
      for (int hh = 0; hh < 2; hh++) {
        float acc[5][4];
#pragma unroll
        for (int i = 0; i < 5; i++) { acc[i][0] = acc[i][1] = acc[i][2] = acc[i][3] = 0.f; }
        const uint32_t so = 32 + lane * 32 + hh * 16;
        band<3, 8, 4, 9, -1, 32, TP_W9 + 288>(acc, tp, ea + so + E_W9, za, lane);
        band<3, 8, 4, 9, 0, 32, TP_W7 + 288>(acc, tp, za + so + L_W7 - 16, za, lane);
        char* a = lb + L_Y + 2 * L_YB + 4 * (16 * g + 8 * hh + 2 * cc);
#pragma unroll
        for (int I = 3; I < 8; I++) {
          SM_F2(a + 1040 * (I - 3)) = make_float2(acc[I - 3][0], acc[I - 3][1]);
          SM_F2(a + 1040 * (I - 3) + 512) = make_float2(acc[I - 3][2], acc[I - 3][3]);
        }
      }
    }
  }
  asm volatile("fence.proxy.async.shared::cta;" ::: "memory");
  __syncthreads();
  DBG_S(6);
  if (lane == 0) {
    if (bid >= 128) {
      if (pass < 3 && (warp & 1) == 0) {
        mbar_expect_tx(bars + B_U, 4096);
        tma2d(sb + xg_off(warp >> 1), tm.x, (d0 + 4) & ~7, (warp >> 1) * 256, bars + B_U);
      }
    } else if (warp < 6) {
      mbar_expect_tx(bars + B_FULL + 8 * warp, STAGE_BYTES);
      tma3d(sb + OFF_ST + warp * STAGE_BYTES, tm.w1, 0, warp * 64, f * 18, bars + B_FULL + 8 * warp);
    } else if (warp < 8) {
      wait_flag(&sc.flags[256 + m], 8);
      mbar_expect_tx(bars + B_X + 8 * (warp - 6), 16384);
      tma2d(sb + (warp - 6) * 16384, tm.xn, (warp - 6) * 64, m * 128, bars + B_X + 8 * (warp - 6));
    }
  }
  __syncwarp();
  uint32_t pnext[8];
#pragma unroll
  for (int i = 0; i < 8; i++) pnext[i] = 0;
  if (bid >= 128 && pass < 3) load_params(pnext, ar, d0 + 4 + ch, n);
  {
    const float4 kb = SM_F4(lb + L_KB);
    const uint32_t dk = pack_bf16(kb.z, kb.z);
#pragma unroll
    for (int k = 0; k < 4; k++) {
      const int t0 = n * 4 + 512 * k;
      char* ya = lb + L_Y + 4 * (t0 + 4 * (t0 >> 8));
      float4 y = SM_F4(ya);
      if (k > 0 || t0 >= 128) { const float4 b = SM_F4(ya + L_YB); y.x += b.x; y.y += b.y; y.z += b.z; y.w += b.w; }
      if (k > 1 || (k == 1 && t0 >= 768)) {
        const float4 b = SM_F4(ya + 2 * L_YB - 3120);
        y.x += b.x; y.y += b.y; y.z += b.z; y.w += b.w;
        if (k > 1 || t0 >= 1020) {
          const char* wp = lb + L_W7 + 32 + 2 * (t0 - 1026);
          const uint32_t wl = *(const uint32_t*)wp, wm = *(const uint32_t*)(wp + 4), wh = *(const uint32_t*)(wp + 8);
          y.x = fmaf(kb.x, bf_hi(wl), y.x); y.y = fmaf(kb.x, bf_lo(wm), y.y);
          y.z = fmaf(kb.x, bf_hi(wm), y.z); y.w = fmaf(kb.x, bf_lo(wh), y.w);
          if (k == 3 && n == 127) {
            const uint2 u03 = SM_U2(lb + 528);
            float pre = bf_lo(u03.x);
            y.x = fmaf(kb.y, pre, y.x); pre += bf_hi(u03.x);
            y.y = fmaf(kb.y, pre, y.y); pre += bf_lo(u03.y);
            y.z = fmaf(kb.y, pre, y.z); pre += bf_hi(u03.y);
            y.w = fmaf(kb.y, pre, y.w);
          }
        }
      }
      const uint2 uu = SM_U2(lb + ((t0 >> 8) + 1) * 528 + (t0 & 255) * 2);
      uint2 o;
      o.x = bf2_add(pack_bf16(y.x, y.y), bf2_mul(uu.x, dk));
      o.y = bf2_add(pack_bf16(y.z, y.w), bf2_mul(uu.y, dk));
      *reinterpret_cast<uint2*>(sc.aT + (size_t)(d0 + ch) * L_SEQ + t0) = o;
    }
  }
  if (bid >= 128) SM_U4(sm + tid * 16) = pack_params(pnext);
  asm volatile("fence.proxy.async.shared::cta;" ::: "memory");
  __syncthreads();
  DBG_S(7);
}

__global__ void __cluster_dims__(2, 1, 1) __launch_bounds__(512, 1)
fused_kernel(const __grid_constant__ CUtensorMap tm_x, const __grid_constant__ CUtensorMap tm_w1,
             const __grid_constant__ CUtensorMap tm_w2, const __grid_constant__ CUtensorMap tm_aT,
             const __grid_constant__ CUtensorMap tm_xn, const __grid_constant__ CUtensorMap tm_out,
             const __grid_constant__ CUtensorMap tm_a8,
             const __grid_constant__ Args ar, const __grid_constant__ Scratch sc) {
  extern __shared__ __align__(1024) char smem_raw[];
  DBG_G(28);
  const uint32_t sb = (smem_u32(smem_raw) + 1023) & ~1023u;
  char* sm = smem_raw + (sb - smem_u32(smem_raw));
  const uint32_t bars = sb + OFF_BAR;
  const int tid = threadIdx.x, lane = tid & 31;
  const int warp = __shfl_sync(0xffffffffu, tid >> 5, 0), wg = warp >> 2;
  const int bid = blockIdx.x;
  const int m = bid >> 3, f = bid & 7, rank = f & 1, pr = f >> 1;

  if (lane == 0) {
    if (warp == 8) {
#pragma unroll
      for (int i = 0; i < B_EMPTY / 8; i++) mbar_init(bars + i * 8, 1);
      asm volatile("fence.mbarrier_init.release.cluster;" ::: "memory");
#pragma unroll
      for (int i = 0; i < 4; i++) mbar_expect_tx(bars + B_RB + 8 * i, 16384);
    } else if (warp == 9) {
#pragma unroll
      for (int i = B_EMPTY / 8; i < NBARS; i++) mbar_init(bars + i * 8, 8);
      asm volatile("fence.mbarrier_init.release.cluster;" ::: "memory");
    } else if (warp == 10) {
      asm volatile("prefetch.tensormap [%0];" ::"l"(&tm_x) : "memory");
    } else if (warp == 11) {
      *reinterpret_cast<Args*>(sm + OFF_ARGS) = ar;
      *reinterpret_cast<Scratch*>(sm + OFF_ARGS + 128) = sc;
    }
  }
  __syncthreads();
  asm volatile("barrier.cluster.arrive.relaxed.aligned;" ::: "memory");

  {
    Maps tm;
    tm.x = &tm_x; tm.w1 = &tm_w1; tm.xn = &tm_xn;
    const int npass = bid < 128 ? 1 : 4;
    const int dbase = bid < 128 ? bid * 4 : 512 + (bid - 128) * 16;
#pragma unroll 1
    for (int pass = 0; pass < npass; pass++)
      ssm_pass(tm, sm, dbase + pass * 4, pass
      );
  }
  if (bid >= 128) {
    if (tid == 0) {
      asm volatile("fence.acq_rel.gpu;" ::: "memory");
      atomicAdd(&sc.flags[304], 1u);
    }
    __syncwarp();
    asm volatile("barrier.cluster.wait.acquire.aligned;" ::: "memory");
    return;
  }

  const uint32_t rdelta = mapa(sb, rank ^ 1) - sb;
  if (wg >= 2) {
    asm volatile("setmaxnreg.dec.sync.aligned.u32 24;");
    asm volatile("barrier.cluster.wait.acquire.aligned;" ::: "memory");
    const int pw = warp - 8;
    if (lane == 0) {
      if (pw < 2) {
        int slot = pw, par = 0;
#pragma unroll 1
        for (int it = 6 + pw; it < 54; it += 2) {
          const int ch = it / 9, s = it - ch * 9;
          const uint32_t fb = bars + B_FULL + 8 * slot;
          mbar_wait(bars + B_EMPTY + 8 * slot, par);
          mbar_expect_tx(fb, STAGE_BYTES);
          tma3d(sb + OFF_ST + slot * STAGE_BYTES, &tm_w1, 0, s * 64, f * 18 + ch * 3, fb);
          slot += 2;
          if (slot >= 6) { slot -= 6; par ^= 1; }
        }
#pragma unroll 1
        for (int pos = 0; pos < 9; pos++) {
          const int chunk = chunk_of(pos, pr, rank);
#pragma unroll 1
          for (slot = pw; slot < 6; slot += 2) {
            const uint32_t fb = bars + B_FULL + 8 * slot;
            mbar_wait(bars + B_EMPTY + 8 * slot, par);
            mbar_expect_tx(fb, STAGE_BYTES);
            tma2d(sb + OFF_ST + slot * STAGE_BYTES, &tm_w2, chunk * 64, f * 576 + slot * 96, fb);
          }
          par ^= 1;
        }
        if (pw == 0) {
          wait_flag(&sc.flags[288 + f * 2], 16);
          mbar_wait(bars + B_EMPTY, par);
          mbar_wait(bars + B_EMPTY + 8, par);
          mbar_expect_tx(bars + B_FULL, 16384);
          tma2d(sb + OFF_ST, &tm_aT, m * 128, f * 64, bars + B_FULL);
          tma2d(sb + OFF_ST + 8192, &tm_aT, m * 128 + 64, f * 64, bars + B_FULL);
          if (atomicAdd(&sc.flags[289 + f * 2], 1u) == 15) { sc.flags[288 + f * 2] = 0; sc.flags[289 + f * 2] = 0; }
        }
      } else if (pw == 2) {
        mbar_wait(bars + B_P1R, 0);
#pragma unroll 1
        for (int k = 0; k < 4; k++) {
          mbar_wait(bars + B_TS + 8 * k, 0);
          bulk_s2peer(sb + k * 16384 + rdelta, sb + OFF_STG + k * 16384, 16384, bars + B_RB + 8 * k + rdelta);
        }
#pragma unroll 1
        for (int k = 0; k < 4; k++) mbar_wait(bars + B_RB + 8 * k, 0);
        mbar_arrive_remote(bars + B_FIN + rdelta);
        mbar_wait(bars + B_FIN, 0);
      } else if (pw == 3) {
        mbar_wait(bars + B_TS8, 0);
        bulk_s2g_release(sc.slots8 + (size_t)(m * 8 + f) * 4096, sb + OFF_C8, 16384);
#pragma unroll 1
        for (int i = 0; i < 8; i++) atomicAdd(&sc.flags[m * 16 + 8 + i], 1u);
#pragma unroll 1
        for (int k = 0; k < 3; k++) {
          const int chunk = 2 * ((pr + k + 1) & 3) + rank;
          mbar_wait(bars + B_TR + 8 * k, 0);
          bulk_s2g_release(sc.slots + (size_t)((m * 8 + chunk) * 3 + k) * 4096, sb + k * 16384, 16384);
          atomicAdd(&sc.flags[m * 16 + chunk], 1u);
          DBG_H(16 + k);
          if (k == 0) {
            mbar_expect_tx(bars + B_OWN, 65536);
            wait_flag(&sc.flags[m * 16 + 8 + f], 8);
            sc.flags[m * 16 + 8 + f] = 0;
#pragma unroll 1
            for (int i = 0; i < 8; i++)
              bulk_g2s(sb + OFF_C8 + i * 2048, sc.slots8 + (size_t)(m * 8 + i) * 4096 + f * 512, 2048, bars + B_OWN);
          }
        }
        wait_flag(&sc.flags[m * 16 + f], 3);
        sc.flags[m * 16 + f] = 0;
        bulk_g2s(sb, sc.slots + (size_t)((m * 8 + f) * 3) * 4096, 49152, bars + B_OWN);
        if (f == 0) sc.flags[256 + m] = 0;
        DBG_H(19);
      } else if (pw == 4) {
        asm volatile("fence.acq_rel.gpu;" ::: "memory");
        atomicAdd(&sc.flags[288 + (bid >> 4) * 2], 1u);
        mbar_wait(bars + B_TR + 8, 0);
        wait_flag(&sc.flags[304], 4);
        mbar_expect_tx(bars + B_A8, 2048);
        tma2d(sb + OFF_A8, &tm_a8, m * 128, 512 + f * 8, bars + B_A8);
        if (atomicAdd(&sc.flags[305], 1u) == 127) { sc.flags[304] = 0; sc.flags[305] = 0; }
      } else {
#pragma unroll 1
        for (int kb = pw - 3; kb < 9; kb += 3) {
          mbar_expect_tx(bars + B_X + 8 * kb, kb == 8 ? 16384 + 2304 : 16384);
          tma2d(sb + kb * 16384, &tm_xn, kb * 64, m * 128, bars + B_X + 8 * kb);
          if (kb == 8) {
            bulk_g2s(sb + OFF_B1, ar.b1 + f * 576, 1152, bars + B_X + 64);
            bulk_g2s(sb + OFF_B2, ar.b2, 1152, bars + B_X + 64);
          }
        }
      }
    }
  } else {
    asm volatile("setmaxnreg.inc.sync.aligned.u32 232;");
    const int wi = warp & 3;
    DBG_T(0);
    MlpCtx c;
    c.bars = bars; c.lane = lane;
    c.dA = (((sb + wg * 8192) & 0x3FFFF) >> 4) | (1u << 16);
    c.dB = ((sb + OFF_ST) & 0x3FFFF) >> 4;

    uint32_t h[144];
    float acc2a[32], acc2b[32];
    {
      float accA[48], accB[48];
#pragma unroll
      for (int i = 0; i < 48; i++) { accA[i] = 0.f; accB[i] = 0.f; }
#pragma unroll
      for (int i = 0; i < 144; i++) h[i] = 0;
      uint32_t baddr = sb + OFF_B1 + (lane & 3) * 4 - 192;
#pragma unroll 1
      for (int j = 0; j < 3; j++) {
        DBG_T(11 + 2 * j);
        p1_chunk<0>(c, j, baddr, accA, accB, h);
        baddr += 192;
        DBG_T(10 + 2 * j);
        p1_chunk<9>(c, j, baddr, accB, accA, h);
        baddr += 192;
      }
      DBG_T(2);
      p2_mma<0>(c, 1, acc2a, h);
      wg_wait<1>();
      stage_release(c, 5);
      fence_regs(accB);
      asm volatile("barrier.cluster.wait.acquire.aligned;" ::: "memory");
      if (lane == 0) { mbar_arrive(bars + B_P1L); mbar_arrive_remote(bars + B_P1R + rdelta); }
      p2_mma<1>(c, 1, acc2a, h);
      gelu_part<0>(baddr, accB); gelu_part<1>(baddr, accB);
      wg_wait<1>(); stage_release(c, 0);
      p2_mma<2>(c, 1, acc2a, h);
      gelu_part<2>(baddr, accB); gelu_part<3>(baddr, accB);
      wg_wait<1>(); stage_release(c, 1);
      p2_mma<3>(c, 1, acc2a, h);
      gelu_part<4>(baddr, accB);
      wg_wait<1>(); stage_release(c, 2);
      p2_mma<4>(c, 1, acc2a, h);
      gelu_part<5>(baddr, accB);
#pragma unroll
      for (int i = 0; i < 24; i++) h[120 + i] = __float_as_uint(accB[(i >> 2) * 8 + (i & 3)]);
      wg_wait<1>(); stage_release(c, 3);
      p2_mma<5>(c, 1, acc2a, h);
      wg_wait<1>(); stage_release(c, 4);
    }
    const uint32_t lbuf = sb + warp * 2048 + lane * 16;
    mbar_wait(bars + B_P1L, 0);
#pragma unroll 1
    for (int pos = 0; pos < 8; pos++) {
      const bool recv = (0x68 >> pos) & 1;
      const int k = recv ? (pos - 2) >> 1 : (pos + 1) >> 1;
      const int ks = k > 3 ? 3 : k;
      const uint32_t addr = lbuf + ks * 16384 + (recv ? 0 : OFF_STG);
      const uint32_t sig = bars + (recv ? B_TR + 8 * k : pos == 1 ? B_TS8 : B_TS + 8 * ks);
      if (recv) mbar_wait(bars + B_RB + k * 8, 0);
      wg_wait<0>(); stage_release(c, 5);
      fence_regs(acc2a);
      DBG_T(20 + pos);
      if (recv) {
#pragma unroll
        for (int i = 0; i < 4; i++) {
          const float4 r = lds128f(addr + i * 512);
          const uint32_t w0 = __float_as_uint(r.x), w1 = __float_as_uint(r.y), w2 = __float_as_uint(r.z), w3 = __float_as_uint(r.w);
          acc2a[8 * i + 0] += bf_lo(w0); acc2a[8 * i + 1] += bf_hi(w0); acc2a[8 * i + 2] += bf_lo(w1); acc2a[8 * i + 3] += bf_hi(w1);
          acc2a[8 * i + 4] += bf_lo(w2); acc2a[8 * i + 5] += bf_hi(w2); acc2a[8 * i + 6] += bf_lo(w3); acc2a[8 * i + 7] += bf_hi(w3);
        }
      }
      if (pos == 1) {
        const uint32_t a8 = sb + OFF_C8 + warp * 256 + lane * 8;
#pragma unroll
        for (int q = 0; q < 8; q++)
          asm volatile("st.shared.v2.u32 [%0], {%1,%2};" ::"r"(a8 + q * 2048), "r"(pack_bf16(acc2a[4 * q], acc2a[4 * q + 1])),
                       "r"(pack_bf16(acc2a[4 * q + 2], acc2a[4 * q + 3])) : "memory");
      } else {
#pragma unroll
        for (int i = 0; i < 4; i++)
          sts128(addr + i * 512, pack_bf16(acc2a[8 * i], acc2a[8 * i + 1]), pack_bf16(acc2a[8 * i + 2], acc2a[8 * i + 3]),
                 pack_bf16(acc2a[8 * i + 4], acc2a[8 * i + 5]), pack_bf16(acc2a[8 * i + 6], acc2a[8 * i + 7]));
      }
      const uint32_t par = pos & 1;
      p2_mma<0>(c, par, acc2a, h);
      asm volatile("fence.proxy.async.shared::cta;" ::: "memory");
      __syncwarp();
      if (lane == 0) mbar_arrive(sig);
      p2_mma<1>(c, par, acc2a, h);
      wg_wait<1>(); stage_release(c, 0);
      p2_mma<2>(c, par, acc2a, h);
      wg_wait<1>(); stage_release(c, 1);
      p2_mma<3>(c, par, acc2a, h);
      wg_wait<1>(); stage_release(c, 2);
      p2_mma<4>(c, par, acc2a, h);
      wg_wait<1>(); stage_release(c, 3);
      p2_mma<5>(c, par, acc2a, h);
      wg_wait<1>(); stage_release(c, 4);
    }
    DBG_T(3);
    {
      const int g = lane >> 2, cc = lane & 3;
      const int t0 = m * 128 + warp * 16 + g;
      const uint2 ga = __ldcg(&sc.gate[t0]), gb = __ldcg(&sc.gate[t0 + 8]);
#pragma unroll
      for (int i = 0; i < 32; i++) acc2b[i] = 0.f;
      mbar_wait(bars + B_RB + 24, 0);
      mbar_wait(bars + B_OWN, 0);
      DBG_T(8);
#pragma unroll
      for (int k = 0; k < 4; k++) {
#pragma unroll
        for (int i = 0; i < 4; i++) {
          float4 r = lds128f(lbuf + k * 16384 + i * 512);
          const uint32_t w0 = __float_as_uint(r.x), w1 = __float_as_uint(r.y), w2 = __float_as_uint(r.z), w3 = __float_as_uint(r.w);
          acc2b[8 * i + 0] += bf_lo(w0); acc2b[8 * i + 1] += bf_hi(w0); acc2b[8 * i + 2] += bf_lo(w1); acc2b[8 * i + 3] += bf_hi(w1);
          acc2b[8 * i + 4] += bf_lo(w2); acc2b[8 * i + 5] += bf_hi(w2); acc2b[8 * i + 6] += bf_lo(w3); acc2b[8 * i + 7] += bf_hi(w3);
        }
      }
      float c8[4] = {0.f, 0.f, 0.f, 0.f};
#pragma unroll
      for (int i = 0; i < 8; i++) {
        uint32_t w0, w1;
        asm volatile("ld.shared.v2.u32 {%0,%1}, [%2];" : "=r"(w0), "=r"(w1) : "r"(sb + OFF_C8 + i * 2048 + warp * 256 + lane * 8));
        c8[0] += bf_lo(w0); c8[1] += bf_hi(w0); c8[2] += bf_lo(w1); c8[3] += bf_hi(w1);
      }
      DBG_T(9);
      mbar_wait(bars + B_FULL, 0);
      wg_wait<0>();
      fence_regs(acc2a);
      DBG_T(4);
#pragma unroll
      for (int jj = 0; jj < 4; jj++) {
        uint32_t a[4];
        {
          const int dl = 8 * (2 * jj + (lane >> 4)) + (lane & 7);
          const int chk = 2 * wi + ((lane >> 3) & 1);
          ldsm4t(a, sb + OFF_ST + wg * 8192 + dl * 128 + ((chk ^ (dl & 7)) << 4));
        }
        uint32_t o[4];
#pragma unroll
        for (int e = 0; e < 2; e++) {
          const int q = 2 * jj + e;
          uint32_t bb = lds32(sb + OFF_B2 + (f * 64 + q * 8 + cc * 2) * 2);
          uint32_t v0 = bf2_add(pack_bf16(acc2a[4 * q] + acc2b[4 * q], acc2a[4 * q + 1] + acc2b[4 * q + 1]), bb);
          uint32_t v1 = bf2_add(pack_bf16(acc2a[4 * q + 2] + acc2b[4 * q + 2], acc2a[4 * q + 3] + acc2b[4 * q + 3]), bb);
          o[2 * e] = bf2_add(bf2_mul(ga.x, a[2 * e]), bf2_mul(ga.y, v0));
          o[2 * e + 1] = bf2_add(bf2_mul(gb.x, a[2 * e + 1]), bf2_mul(gb.y, v1));
        }
        {
          const int row = (lane & 7) + ((lane >> 3) & 1) * 8;
          const uint32_t addr = sb + 49152 + warp * 2048 + row * 128 + (((2 * jj + (lane >> 4)) ^ (row & 7)) << 4);
          asm volatile("stmatrix.sync.aligned.m8n8.x4.shared.b16 [%0], {%1,%2,%3,%4};"
                       ::"r"(addr), "r"(o[0]), "r"(o[1]), "r"(o[2]), "r"(o[3]) : "memory");
        }
      }
      asm volatile("fence.proxy.async.shared::cta;" ::: "memory");
      __syncwarp();
      if (lane == 0) {
        asm volatile("cp.async.bulk.tensor.2d.global.shared::cta.bulk_group [%0, {%2, %3}], [%1];\n"
                     "cp.async.bulk.commit_group;"
                     ::"l"(&tm_out), "r"(sb + 49152 + warp * 2048), "r"(f * 64), "r"(m * 128 + warp * 16) : "memory");
      }
      __syncwarp();
      mbar_wait(bars + B_A8, 0);
      {
        __nv_bfloat16* op = ar.out + (size_t)t0 * D_MOD + cc * 2 + 512 + f * 8;
        uint32_t a0, a1;
        const uint32_t addr = sb + OFF_A8 + (lane & 7) * 256 + (warp * 2 + ((lane >> 3) & 1)) * 16;
        asm volatile("ldmatrix.sync.aligned.m8n8.x2.trans.shared.b16 {%0,%1}, [%2];" : "=r"(a0), "=r"(a1) : "r"(addr));
        const uint32_t bb = lds32(sb + OFF_B2 + (512 + f * 8 + cc * 2) * 2);
        const uint32_t v0 = bf2_add(pack_bf16(c8[0], c8[1]), bb), v1 = bf2_add(pack_bf16(c8[2], c8[3]), bb);
        *reinterpret_cast<uint32_t*>(op) = bf2_add(bf2_mul(ga.x, a0), bf2_mul(ga.y, v0));
        *reinterpret_cast<uint32_t*>(op + 8 * D_MOD) = bf2_add(bf2_mul(gb.x, a1), bf2_mul(gb.y, v1));
      }
      if (lane == 0) asm volatile("cp.async.bulk.wait_group.read 0;" ::: "memory");
      DBG_T(5);
      DBG_G(29);
    }
  }
}

typedef CUresult (*EncodeTiledFn)(CUtensorMap*, CUtensorMapDataType, cuuint32_t, void*, const cuuint64_t*,
                                  const cuuint64_t*, const cuuint32_t*, const cuuint32_t*, CUtensorMapInterleave,
                                  CUtensorMapSwizzle, CUtensorMapL2promotion, CUtensorMapFloatOOBfill);

static void make_map(EncodeTiledFn enc, CUtensorMap* tm, const void* base, uint64_t inner, uint64_t outer, uint32_t binner,
                     uint32_t bouter, CUtensorMapSwizzle swz) {
  cuuint64_t gd[2] = {inner, outer};
  cuuint64_t gs[1] = {inner * 2};
  cuuint32_t bd[2] = {binner, bouter};
  cuuint32_t es[2] = {1, 1};
  enc(tm, CU_TENSOR_MAP_DATA_TYPE_BFLOAT16, 2, const_cast<void*>(base), gd, gs, bd, es, CU_TENSOR_MAP_INTERLEAVE_NONE, swz,
      CU_TENSOR_MAP_L2_PROMOTION_L2_128B, CU_TENSOR_MAP_FLOAT_OOB_FILL_NONE);
}

extern "C" void kernel_launch(void* const* d_in, const int* in_sizes, int n_in, void* d_out, int out_size) {
  typedef const __nv_bfloat16* BP;
  Args ar;
  ar.u = (BP)d_in[0]; ar.Are = (BP)d_in[1]; ar.Aim = (BP)d_in[2]; ar.Bre = (BP)d_in[3]; ar.Bim = (BP)d_in[4];
  ar.Cre = (BP)d_in[5]; ar.Cim = (BP)d_in[6]; ar.logdt = (BP)d_in[7]; ar.Dskip = (BP)d_in[8];
  ar.w1 = (BP)d_in[10]; ar.b1 = (BP)d_in[11]; ar.w2 = (BP)d_in[12]; ar.b2 = (BP)d_in[13]; ar.gate_w = (BP)d_in[14];
  ar.out = (__nv_bfloat16*)d_out;

  static EncodeTiledFn enc = nullptr;
  static Scratch sc;
  if (!enc) {
    cudaDriverEntryPointQueryResult qr;
    cudaGetDriverEntryPoint("cuTensorMapEncodeTiled", (void**)&enc, cudaEnableDefault, &qr);
    cudaGetSymbolAddress((void**)&sc.aT, g_aT);
    cudaGetSymbolAddress((void**)&sc.xn, g_xn);
    cudaGetSymbolAddress((void**)&sc.gate, g_gate);
    cudaGetSymbolAddress((void**)&sc.slots, g_slots);
    cudaGetSymbolAddress((void**)&sc.slots8, g_slots8);
    cudaGetSymbolAddress((void**)&sc.flags, g_flags);
    sc.dbg = nullptr;
    cudaFuncSetAttribute(fused_kernel, cudaFuncAttributeMaxDynamicSharedMemorySize, SMEM_BYTES);
  }
  CUtensorMap tm_x, tm_w1, tm_w2, tm_aT, tm_xn, tm_out, tm_a8;
  make_map(enc, &tm_a8, sc.aT, L_SEQ, D_MOD, 128, 8, CU_TENSOR_MAP_SWIZZLE_NONE);
  make_map(enc, &tm_x, ar.u, D_MOD, L_SEQ, 8, 256, CU_TENSOR_MAP_SWIZZLE_NONE);
  make_map(enc, &tm_w2, ar.w2, D_MOD, F_HID, 64, 96, CU_TENSOR_MAP_SWIZZLE_128B);
  make_map(enc, &tm_aT, sc.aT, L_SEQ, D_MOD, 64, 64, CU_TENSOR_MAP_SWIZZLE_128B);
  make_map(enc, &tm_xn, sc.xn, D_MOD, L_SEQ, 64, 128, CU_TENSOR_MAP_SWIZZLE_128B);
  make_map(enc, &tm_out, d_out, D_MOD, L_SEQ, 64, 16, CU_TENSOR_MAP_SWIZZLE_128B);
  {
    cuuint64_t gd[3] = {32, D_MOD, F_HID / 32};
    cuuint64_t gs[2] = {F_HID * 2, 64};
    cuuint32_t bd[3] = {32, 64, 3};
    cuuint32_t es[3] = {1, 1, 1};
    enc(&tm_w1, CU_TENSOR_MAP_DATA_TYPE_BFLOAT16, 3, (void*)ar.w1, gd, gs, bd, es, CU_TENSOR_MAP_INTERLEAVE_NONE,
        CU_TENSOR_MAP_SWIZZLE_64B, CU_TENSOR_MAP_L2_PROMOTION_L2_128B, CU_TENSOR_MAP_FLOAT_OOB_FILL_NONE);
  }
  fused_kernel<<<132, 512, SMEM_BYTES, cudaStreamPerThread>>>(tm_x, tm_w1, tm_w2, tm_aT, tm_xn, tm_out, tm_a8, ar, sc);
}
```

```cpp
#include <cuda_runtime.h>
#include <cuda_bf16.h>
#include <cuda.h>
#include <stdint.h>

#define HFENCE() asm volatile("fence.proxy.async.shared::cta;" ::: "memory")
#define L_SEQ 2048
#define D_MOD 576
#define F_HID 4608
#define N_ST 128

__device__ __align__(1024) __nv_bfloat16 g_aT[D_MOD * L_SEQ];
__device__ __align__(1024) __nv_bfloat16 g_xn[L_SEQ * D_MOD];
__device__ __align__(1024) uint32_t g_slots[16 * 8 * 3 * 4096];
__device__ __align__(1024) uint32_t g_slots8[16 * 8 * 4096];
__device__ uint2 g_gate[L_SEQ];
__device__ unsigned int g_flags[320];
struct Scratch {
  __nv_bfloat16* aT; __nv_bfloat16* xn; uint2* gate; uint32_t* slots; uint32_t* slots8; unsigned int* flags;
  long long* dbg;
};
#define DBG_T(i)
#define DBG_S(i)
#define DBG_H(i)
#define DBG_G(i)

__device__ __forceinline__ uint32_t smem_u32(const void* p) { return (uint32_t)__cvta_generic_to_shared(p); }
__device__ __forceinline__ void mbar_init(uint32_t bar, int cnt) {
  asm volatile("mbarrier.init.shared::cta.b64 [%0], %1;" ::"r"(bar), "r"(cnt));
}
__device__ __forceinline__ void mbar_expect_tx(uint32_t bar, uint32_t bytes) {
  asm volatile("mbarrier.arrive.expect_tx.shared::cta.b64 _, [%0], %1;" ::"r"(bar), "r"(bytes) : "memory");
}
__device__ __forceinline__ void mbar_arrive(uint32_t bar) {
  asm volatile("mbarrier.arrive.shared::cta.b64 _, [%0];" ::"r"(bar) : "memory");
}
__device__ __forceinline__ void mbar_arrive_remote(uint32_t remote_bar) {
  asm volatile("mbarrier.arrive.relaxed.cluster.shared::cluster.b64 _, [%0];" ::"r"(remote_bar) : "memory");
}
__device__ __forceinline__ void mbar_wait(uint32_t bar, uint32_t parity) {
  asm volatile(
      "{\n.reg .pred p;\n.reg .u32 n;\nmov.u32 n, 0;\n"
      "W_%=:\nmbarrier.try_wait.parity.shared::cta.b64 p, [%0], %1;\n@p bra D_%=;\n"
      "add.u32 n, n, 1;\nsetp.lt.u32 p, n, 400000;\n@p bra W_%=;\ntrap;\nD_%=:\n}"
      ::"r"(bar), "r"(parity) : "memory");
}
__device__ __forceinline__ void tma2d(uint32_t dst, const CUtensorMap* tm, int c0, int c1, uint32_t bar) {
  asm volatile("cp.async.bulk.tensor.2d.shared::cluster.global.mbarrier::complete_tx::bytes [%0], [%1, {%3, %4}], [%2];"
               ::"r"(dst), "l"(tm), "r"(bar), "r"(c0), "r"(c1) : "memory");
}
__device__ __forceinline__ void wait_flag(unsigned int* flag, unsigned int target) {
  asm volatile(
      "{\n.reg .pred p;\n.reg .u32 n, v;\nmov.u32 n, 0;\n"
      "W_%=:\nld.acquire.gpu.global.u32 v, [%0];\nsetp.ge.u32 p, v, %1;\n@p bra D_%=;\n"
      "nanosleep.u32 32;\nadd.u32 n, n, 1;\nsetp.lt.u32 p, n, 4000000;\n@p bra W_%=;\ntrap;\nD_%=:\n}"
      ::"l"(flag), "r"(target) : "memory");
}
__device__ __forceinline__ void bulk_g2s(uint32_t dst, const void* src, uint32_t bytes, uint32_t bar) {
  asm volatile("cp.async.bulk.shared::cluster.global.mbarrier::complete_tx::bytes [%0], [%1], %2, [%3];"
               ::"r"(dst), "l"(src), "r"(bytes), "r"(bar) : "memory");
}
__device__ __forceinline__ void tma3d(uint32_t dst, const CUtensorMap* tm, int c0, int c1, int c2, uint32_t bar) {
  asm volatile("cp.async.bulk.tensor.3d.shared::cluster.global.mbarrier::complete_tx::bytes [%0], [%1, {%3, %4, %5}], [%2];"
               ::"r"(dst), "l"(tm), "r"(bar), "r"(c0), "r"(c1), "r"(c2) : "memory");
}
__device__ __forceinline__ uint32_t mapa(uint32_t addr, uint32_t rank) {
  uint32_t r;
  asm("mapa.shared::cluster.u32 %0, %1, %2;" : "=r"(r) : "r"(addr), "r"(rank));
  return r;
}
__device__ __forceinline__ float4 lds128f(uint32_t addr) {
  float4 v;
  asm volatile("ld.shared.v4.f32 {%0,%1,%2,%3}, [%4];" : "=f"(v.x), "=f"(v.y), "=f"(v.z), "=f"(v.w) : "r"(addr));
  return v;
}
__device__ __forceinline__ uint32_t lds32(uint32_t addr) {
  uint32_t v;
  asm volatile("ld.shared.u32 %0, [%1];" : "=r"(v) : "r"(addr));
  return v;
}
__device__ __forceinline__ void sts128(uint32_t addr, uint32_t a, uint32_t b, uint32_t c, uint32_t d) {
  asm volatile("st.shared.v4.u32 [%0], {%1,%2,%3,%4};" ::"r"(addr), "r"(a), "r"(b), "r"(c), "r"(d) : "memory");
}
#define WG_FENCE() asm volatile("wgmma.fence.sync.aligned;" ::: "memory")
#define WG_COMMIT() asm volatile("wgmma.commit_group.sync.aligned;" ::: "memory")
template <int n> __device__ __forceinline__ void wg_wait() {
  asm volatile("wgmma.wait_group.sync.aligned %0;" ::"n"(n) : "memory");
}
__device__ __forceinline__ uint32_t pack_bf16(float lo, float hi) {
  uint32_t r;
  asm("cvt.rn.bf16x2.f32 %0, %1, %2;" : "=r"(r) : "f"(hi), "f"(lo));
  return r;
}
__device__ __forceinline__ float bf_lo(uint32_t p) { return __uint_as_float(p << 16); }
__device__ __forceinline__ float bf_hi(uint32_t p) { return __uint_as_float(p & 0xffff0000u); }
__device__ __forceinline__ float bf_round(float x) { return __bfloat162float(__float2bfloat16_rn(x)); }
__device__ __forceinline__ uint32_t bf2_add(uint32_t a, uint32_t b) {
  uint32_t r;
  asm("add.rn.bf16x2 %0, %1, %2;" : "=r"(r) : "r"(a), "r"(b));
  return r;
}
__device__ __forceinline__ uint32_t bf2_mul(uint32_t a, uint32_t b) {
  uint32_t r;
  asm("mul.rn.bf16x2 %0, %1, %2;" : "=r"(r) : "r"(a), "r"(b));
  return r;
}
__device__ __forceinline__ float tanh_fast(float x) {
  float r;
  asm("tanh.approx.f32 %0, %1;" : "=f"(r) : "f"(x));
  return r;
}
__device__ __forceinline__ uint32_t bf2_fma(uint32_t a, uint32_t b, uint32_t c) {
  uint32_t r;
  asm("fma.rn.bf16x2 %0, %1, %2, %3;" : "=r"(r) : "r"(a), "r"(b), "r"(c));
  return r;
}
__device__ __forceinline__ float gelu_half(float hv) {
  const float p = fmaf(hv * hv, 8.0f * 0.0356774081363f, 2.0f * 0.7978845608029f);
  return fmaf(hv, tanh_fast(hv * p), hv);
}
__device__ __forceinline__ uint32_t gelu_pack(float a0, float a1, uint32_t hbias2) {
  const uint32_t hp = bf2_fma(pack_bf16(a0, a1), 0x3f003f00u, hbias2);
  return pack_bf16(gelu_half(bf_lo(hp)), gelu_half(bf_hi(hp)));
}

#define R8(a, o) "+f"(a[o]), "+f"(a[o + 1]), "+f"(a[o + 2]), "+f"(a[o + 3]), "+f"(a[o + 4]), "+f"(a[o + 5]), "+f"(a[o + 6]), "+f"(a[o + 7])
#define W8(a, o) "=f"(a[o]), "=f"(a[o + 1]), "=f"(a[o + 2]), "=f"(a[o + 3]), "=f"(a[o + 4]), "=f"(a[o + 5]), "=f"(a[o + 6]), "=f"(a[o + 7])
#define REGS48 "{%0,%1,%2,%3,%4,%5,%6,%7,%8,%9,%10,%11,%12,%13,%14,%15,%16,%17,%18,%19,%20,%21,%22,%23," \
               "%24,%25,%26,%27,%28,%29,%30,%31,%32,%33,%34,%35,%36,%37,%38,%39,%40,%41,%42,%43,%44,%45,%46,%47}"
#define REGS32 "{%0,%1,%2,%3,%4,%5,%6,%7,%8,%9,%10,%11,%12,%13,%14,%15,%16,%17,%18,%19,%20,%21,%22,%23," \
               "%24,%25,%26,%27,%28,%29,%30,%31}"
#define DESC_HI_A  "0x40000040"
#define DESC_HI_B1 "0x80000020"
#define DESC_HI_B2 "0x40000040"
template <bool ACC, int OA, int OB>
__device__ __forceinline__ void wgmma_ss_n96(float (&d)[48], uint32_t da, uint32_t db) {
  if (ACC)
    asm volatile("{\n.reg .b64 xa, xb;\n.reg .b32 la, lb;\nadd.u32 la, %48, %50;\nadd.u32 lb, %49, %51;\n"
                 "mov.b64 xa, {la, " DESC_HI_A "};\nmov.b64 xb, {lb, " DESC_HI_B1 "};\n"
                 "wgmma.mma_async.sync.aligned.m64n96k16.f32.bf16.bf16 " REGS48 ", xa, xb, 1, 1, 1, 0, 1;\n}\n"
                 : R8(d, 0), R8(d, 8), R8(d, 16), R8(d, 24), R8(d, 32), R8(d, 40) : "r"(da), "r"(db), "n"(OA), "n"(OB));
  else
    asm volatile("{\n.reg .b64 xa, xb;\n.reg .b32 la, lb;\nadd.u32 la, %48, %50;\nadd.u32 lb, %49, %51;\n"
                 "mov.b64 xa, {la, " DESC_HI_A "};\nmov.b64 xb, {lb, " DESC_HI_B1 "};\n"
                 "wgmma.mma_async.sync.aligned.m64n96k16.f32.bf16.bf16 " REGS48 ", xa, xb, 0, 1, 1, 0, 1;\n}\n"
                 : W8(d, 0), W8(d, 8), W8(d, 16), W8(d, 24), W8(d, 32), W8(d, 40) : "r"(da), "r"(db), "n"(OA), "n"(OB));
}
template <bool ACC, int OB>
__device__ __forceinline__ void wgmma_rs_n64(float (&d)[32], uint32_t a0, uint32_t a1, uint32_t a2, uint32_t a3, uint32_t db) {
  if (ACC)
    asm volatile("{\n.reg .b64 xb;\n.reg .b32 lb;\nadd.u32 lb, %36, %37;\nmov.b64 xb, {lb, " DESC_HI_B2 "};\n"
                 "wgmma.mma_async.sync.aligned.m64n64k16.f32.bf16.bf16 " REGS32 ", {%32,%33,%34,%35}, xb, 1, 1, 1, 1;\n}\n"
                 : R8(d, 0), R8(d, 8), R8(d, 16), R8(d, 24) : "r"(a0), "r"(a1), "r"(a2), "r"(a3), "r"(db), "n"(OB));
  else
    asm volatile("{\n.reg .b64 xb;\n.reg .b32 lb;\nadd.u32 lb, %36, %37;\nmov.b64 xb, {lb, " DESC_HI_B2 "};\n"
                 "wgmma.mma_async.sync.aligned.m64n64k16.f32.bf16.bf16 " REGS32 ", {%32,%33,%34,%35}, xb, 0, 1, 1, 1;\n}\n"
                 : W8(d, 0), W8(d, 8), W8(d, 16), W8(d, 24) : "r"(a0), "r"(a1), "r"(a2), "r"(a3), "r"(db), "n"(OB));
}
template <int N> __device__ __forceinline__ void fence_regs(float (&d)[N]) {
#pragma unroll
  for (int i = 0; i < N; i++) asm volatile("" : "+f"(d[i])::"memory");
}

constexpr int XS_BYTES = 9 * 16384;
constexpr int STAGE_BYTES = 12288;
constexpr int OFF_ST = XS_BYTES;
constexpr int OFF_B1 = OFF_ST + 6 * STAGE_BYTES;
constexpr int OFF_B2 = OFF_B1 + 1152;
constexpr int OFF_BAR = OFF_B2 + 1152;
constexpr int B_FULL = 0, B_X = 48  , B_RB = 120  , B_OWN = 152, B_FIN = 160, B_A8 = 168,
              B_EMPTY = 176  , B_TS = 224  , B_TS8 = 256, B_TR = 264  , B_P1L = 288, B_P1R = 296, B_U = 304,
              NBARS = 39;
constexpr int OFF_A8 = OFF_BAR + 512;
constexpr int OFF_ARGS = OFF_A8 + 2048;
constexpr int SMEM_BYTES = OFF_ARGS + 256 + 1024;
constexpr int OFF_STG = 65536, OFF_C8 = 131072;
constexpr int E_UA = 0, E_UB = 3616, E_W3A = 7232, E_W3B = 10848, E_W5 = 14464, E_W9 = 17568, E_TAP = 19680, E_SIZE = 23392;
constexpr int L_W7 = 4752, L_KB = 6832, L_Y = 6848, L_YB = 8304, L_SIZE = 28656;
constexpr int L_CONST = L_Y, L_KC = L_Y + 10240;
constexpr int TP_0 = 0, TP_W3A = 580, TP_UA = 716, TP_UB = 852, TP_W3B = 988, TP_W5 = 1248, TP_W9 = 1448, TP_W7 = 1648,
              TP_COPY = 1856;
__device__ __forceinline__ int e_off(int ch) { return ch == 0 ? 0 : OFF_ST + (ch - 1) * E_SIZE; }
__device__ __forceinline__ int l_off(int ch) { return 32768 + ch * L_SIZE; }
__device__ __forceinline__ int xg_off(int box) { return box < 4 ? OFF_ST + box * 4096 : 170880 + (box - 4) * 4096; }

__device__ __forceinline__ void ln_load(const __nv_bfloat16* __restrict__ x, const __nv_bfloat16* __restrict__ gate_w,
                                        int row, int lane, uint32_t (&w)[9], uint32_t (&gw)[9]) {
  const uint32_t* xr = reinterpret_cast<const uint32_t*>(x + (size_t)row * D_MOD) + lane;
  const uint32_t* gwp = reinterpret_cast<const uint32_t*>(gate_w) + lane;
#pragma unroll
  for (int j = 0; j < 9; j++) {
    asm volatile("ld.global.nc.u32 %0, [%1];" : "=r"(w[j]) : "l"(xr + j * 32));
    asm volatile("ld.global.nc.u32 %0, [%1];" : "=r"(gw[j]) : "l"(gwp + j * 32));
  }
}
__device__ __forceinline__ void ln_row(int row, int lane, const Scratch& sc, const uint32_t (&w)[9], const uint32_t (&gw)[9]) {
  float s = 0.f, gsum = 0.f;
#pragma unroll
  for (int j = 0; j < 9; j++) {
    uint32_t pr2 = bf2_mul(w[j], gw[j]);
    s += bf_lo(w[j]) + bf_hi(w[j]);
    gsum += bf_lo(pr2) + bf_hi(pr2);
  }
#pragma unroll
  for (int o = 1; o < 32; o <<= 1) { s += __shfl_xor_sync(~0u, s, o); gsum += __shfl_xor_sync(~0u, gsum, o); }
  const float mean = s * (1.0f / 576.0f);
  float vs = 0.f;
#pragma unroll
  for (int j = 0; j < 9; j++) {
    float d0 = bf_lo(w[j]) - mean, d1 = bf_hi(w[j]) - mean;
    vs = fmaf(d0, d0, vs); vs = fmaf(d1, d1, vs);
  }
#pragma unroll
  for (int o = 1; o < 32; o <<= 1) vs += __shfl_xor_sync(~0u, vs, o);
  const float mb = bf_round(mean);
  const float vb = bf_round(vs * (1.0f / 576.0f));
  const float rinv = __frcp_rn(bf_round(__fsqrt_rn(bf_round(vb + 1e-5f))));
  const uint32_t nm2 = pack_bf16(-mb, -mb);
  uint32_t* dst = reinterpret_cast<uint32_t*>(sc.xn + (size_t)row * D_MOD) + lane;
#pragma unroll
  for (int j = 0; j < 9; j++) {
    uint32_t dd = bf2_add(w[j], nm2);
    dst[j * 32] = pack_bf16(bf_lo(dd) * rinv, bf_hi(dd) * rinv);
  }
  if (lane == 0) {
    float gv = bf_round(__fdividef(1.0f, 1.0f + __expf(-bf_round(gsum))));
    float og = bf_round(1.0f - gv);
    sc.gate[row] = make_uint2(pack_bf16(gv, gv), pack_bf16(og, og));
  }
}
__device__ __forceinline__ void mma_bf16(float (&d)[4], uint32_t a0, uint32_t a1, uint32_t a2, uint32_t a3, uint32_t b0, uint32_t b1) {
  asm("mma.sync.aligned.m16n8k16.row.col.f32.bf16.bf16.f32 {%0,%1,%2,%3}, {%4,%5,%6,%7}, {%8,%9}, {%0,%1,%2,%3};"
      : "+f"(d[0]), "+f"(d[1]), "+f"(d[2]), "+f"(d[3]) : "r"(a0), "r"(a1), "r"(a2), "r"(a3), "r"(b0), "r"(b1));
}
__device__ __forceinline__ void mma_tf32(float (&d)[4], float a0, float a1, float a2, float a3, float b0, float b1) {
  asm("mma.sync.aligned.m16n8k8.row.col.f32.tf32.tf32.f32 {%0,%1,%2,%3}, {%4,%5,%6,%7}, {%8,%9}, {%0,%1,%2,%3};"
      : "+f"(d[0]), "+f"(d[1]), "+f"(d[2]), "+f"(d[3])
      : "r"(__float_as_uint(a0)), "r"(__float_as_uint(a1)), "r"(__float_as_uint(a2)), "r"(__float_as_uint(a3)),
        "r"(__float_as_uint(b0)), "r"(__float_as_uint(b1)));
}
__device__ __forceinline__ float2 cexp_l(float al, float th, float l) {
  float mg;
  asm("ex2.approx.ftz.f32 %0, %1;" : "=f"(mg) : "f"(al * l));
  const float tr = th * l;
  return make_float2(mg * __cosf(tr), mg * __sinf(tr));
}
__device__ __forceinline__ float2 cmul(float2 a, float2 b) {
  return make_float2(fmaf(a.x, b.x, -a.y * b.y), fmaf(a.x, b.y, a.y * b.x));
}
__device__ __forceinline__ float2 cmulc(float2 a, float2 b) {
  return make_float2(fmaf(a.x, b.x, -a.y * b.y), fmaf(-a.x, b.y, -a.y * b.x));
}
__device__ __forceinline__ float2 csq(float2 a) { return make_float2(fmaf(a.x, a.x, -a.y * a.y), 2.0f * a.x * a.y); }
#define SM_U32(p) (*reinterpret_cast<uint32_t*>(p))
#define SM_F32(p) (*reinterpret_cast<float*>(p))
#define SM_U16(p) (*reinterpret_cast<unsigned short*>(p))
#define SM_U2(p) (*reinterpret_cast<uint2*>(p))
#define SM_F2(p) (*reinterpret_cast<float2*>(p))
#define SM_U4(p) (*reinterpret_cast<uint4*>(p))
#define SM_F4(p) (*reinterpret_cast<float4*>(p))
template <int OFF, int TAG>
__device__ __forceinline__ uint32_t lds_free(uint32_t base) {
  uint32_t v;
  asm volatile("ld.volatile.shared.u32 %0, [%1+%2]; // %3" : "=r"(v) : "r"(base), "n"(OFF), "n"(TAG));
  return v;
}
template <int K0, int K1, int OFF, int K>
__device__ __forceinline__ void load_tquads_(uint32_t (&q)[K1 - K0][4], uint32_t tp) {
  if constexpr (K >= K0) {
    q[K - K0][0] = lds_free<OFF - 32 * K, 0>(tp);
    q[K - K0][1] = lds_free<OFF - 32 * K - 16, 1>(tp);
    q[K - K0][2] = lds_free<OFF - 32 * K + 16, 2>(tp);
    q[K - K0][3] = lds_free<OFF - 32 * K, 3>(tp);
    load_tquads_<K0, K1, OFF, K - 1>(q, tp);
  }
}
template <int K0, int K1, int OFF>
__device__ __forceinline__ void load_tquads(uint32_t (&q)[K1 - K0][4], uint32_t tp) {
  load_tquads_<K0, K1, OFF, K1 - 1>(q, tp);
}
__device__ __forceinline__ void ldsm4_free(uint32_t (&r)[4], uint32_t addr) {
  asm("ldmatrix.sync.aligned.m8n8.x4.shared.b16 {%0,%1,%2,%3}, [%4];"
      : "=r"(r[0]), "=r"(r[1]), "=r"(r[2]), "=r"(r[3]) : "r"(addr));
}
__device__ __forceinline__ void ldsm4t_free(uint32_t (&r)[4], uint32_t addr) {
  asm("ldmatrix.sync.aligned.m8n8.x4.trans.shared.b16 {%0,%1,%2,%3}, [%4];"
      : "=r"(r[0]), "=r"(r[1]), "=r"(r[2]), "=r"(r[3]) : "r"(addr));
}
__device__ __forceinline__ uint32_t ldg_u16(const __nv_bfloat16* p) {
  unsigned short v;
  asm volatile("ld.global.nc.u16 %0, [%1];" : "=h"(v) : "l"(p));
  return v;
}
__device__ __forceinline__ void ldsm4t(uint32_t (&r)[4], uint32_t addr) {
  asm volatile("ldmatrix.sync.aligned.m8n8.x4.trans.shared.b16 {%0,%1,%2,%3}, [%4];"
               : "=r"(r[0]), "=r"(r[1]), "=r"(r[2]), "=r"(r[3]) : "r"(addr) : "memory");
}
template <int I0, int I1, int K0, int K1, int JMIN, int RB, int TOFF>
__device__ __forceinline__ void band(float (&acc)[I1 - I0][4], uint32_t tp, uint32_t sa, uint32_t za, int lane) {
  uint32_t tq[K1 - K0][4];
  load_tquads<K0, K1, TOFF>(tq, tp);
  constexpr int JL = (I0 - K1 + 1 > JMIN) ? I0 - K1 + 1 : JMIN, JH = I1 - 1 - K0;
  constexpr int JP = (JL >= 0) ? (JL & ~1) : -2;
#pragma unroll
  for (int J2 = JP; J2 <= JH; J2 += 2) {
    uint32_t b[4];
    ldsm4t_free(b, (J2 < 0 && lane < 31) ? za : sa + J2 * 16 * RB);
#pragma unroll
    for (int hf = 0; hf < 2; hf++) {
      const int J = J2 + hf;
#pragma unroll
      for (int k = K0; k < K1; k++) {
        const int I = J + k;
        if (J >= JL && J <= JH && I >= I0 && I < I1)
          mma_bf16(acc[I - I0], tq[k - K0][0], tq[k - K0][1], tq[k - K0][2], tq[k - K0][3], b[2 * hf], b[2 * hf + 1]);
      }
    }
  }
}
template <int I0, int I1>
__device__ __forceinline__ void p8_tiles(uint32_t ea, uint32_t za, char* lb, uint32_t tp, int lane) {
  float acc[I1 - I0][4];
#pragma unroll
  for (int i = 0; i < I1 - I0; i++) { acc[i][0] = acc[i][1] = acc[i][2] = acc[i][3] = 0.f; }
  const uint32_t sa = ea + 32 + lane * 16;
  band<I0, I1, 2, 5, -1, 16, TP_W3A + 160>(acc, tp, sa + E_W3A, za, lane);
  band<I0, I1, 2, 5, 0, 16, TP_UA + 160>(acc, tp, sa + E_UA, za, lane);
  band<I0, I1, 2, 5, 0, 16, TP_UB + 160>(acc, tp, sa + E_UB, za, lane);
  band<I0, I1, 2, 9, 0, 16, TP_W3B + 288>(acc, tp, sa + E_W3B, za, lane);
  band<I0, I1, 4, 9, -1, 16, TP_W5 + 288>(acc, tp, sa + E_W5, za, lane);
  char* a = lb + L_Y + L_YB + 4 * (8 * (lane >> 2) + 2 * (lane & 3));
#pragma unroll
  for (int I = I0; I < I1; I++) {
    SM_F2(a + 4 * (128 * I + 4 * (I >> 1))) = make_float2(acc[I - I0][0], acc[I - I0][1]);
    SM_F2(a + 4 * (128 * I + 4 * (I >> 1)) + 256) = make_float2(acc[I - I0][2], acc[I - I0][3]);
  }
}

struct MlpCtx {
  uint32_t bars;
  uint32_t dA, dB;
  int lane;
};
__device__ __forceinline__ void stage_release(const MlpCtx& c, int slot) {
  if (c.lane == 0) mbar_arrive(c.bars + B_EMPTY + 8 * slot);
}
template <int P>
__device__ __forceinline__ void gelu_part(uint32_t baddr, float (&acc)[48]) {
  asm volatile("" : R8(acc, P * 8)::"memory");
  const uint32_t b0 = bf2_mul(lds32(baddr + P * 32), 0x3f003f00u), b1 = bf2_mul(lds32(baddr + P * 32 + 16), 0x3f003f00u);
  uint32_t r0 = gelu_pack(acc[P * 8 + 0], acc[P * 8 + 1], b0);
  uint32_t r1 = gelu_pack(acc[P * 8 + 2], acc[P * 8 + 3], b0);
  uint32_t r2 = gelu_pack(acc[P * 8 + 4], acc[P * 8 + 5], b1);
  uint32_t r3 = gelu_pack(acc[P * 8 + 6], acc[P * 8 + 7], b1);
  acc[P * 8 + 0] = __uint_as_float(r0);
  acc[P * 8 + 1] = __uint_as_float(r1);
  acc[P * 8 + 2] = __uint_as_float(r2);
  acc[P * 8 + 3] = __uint_as_float(r3);
}
__device__ __forceinline__ void h_push(uint32_t (&h)[144], float (&acc)[48]) {
  asm volatile("" : R8(acc, 0)::"memory");
#pragma unroll
  for (int i = 0; i < 96; i++) h[i] = h[i + 24];
#pragma unroll
  for (int i = 0; i < 24; i++) h[96 + i] = __float_as_uint(acc[(i >> 2) * 8 + (i & 3)]);
}
template <int SB, int I>
__device__ __forceinline__ void p1_mma(const MlpCtx& c, float (&cur)[48]) {
  constexpr int S = SB % 9;
  wgmma_ss_n96<(S | I) != 0, ((S * 16384 + I * 32) >> 4),
               (4096 >> 4 << 16) + (((SB % 6) * STAGE_BYTES + I * 1024) >> 4)>(cur, c.dA, c.dB);
}
template <int SB>
__device__ __forceinline__ void p1_stage(const MlpCtx& c, int j, uint32_t baddr, float (&cur)[48], float (&prev)[48],
                                         uint32_t (&h)[144]) {
  constexpr int S = SB % 9;
  if (SB < 9) mbar_wait(c.bars + B_X + 8 * S, 0);
  mbar_wait(c.bars + B_FULL + 8 * (SB % 6), ((SB / 6) + j) & 1);
  WG_FENCE();
  p1_mma<SB, 0>(c, cur); p1_mma<SB, 1>(c, cur); p1_mma<SB, 2>(c, cur); p1_mma<SB, 3>(c, cur);
  WG_COMMIT();
  if (S >= 1 && S <= 6) gelu_part<(S >= 1 && S <= 6) ? S - 1 : 0>(baddr, prev);
  if (S == 7) h_push(h, prev);
  wg_wait<1>();
  if (SB > 0 || j > 0) stage_release(c, (SB + 5) % 6);
  if (S == 0) fence_regs(prev);
}
template <int SB0>
__device__ __forceinline__ void p1_chunk(const MlpCtx& c, int j, uint32_t baddr, float (&cur)[48], float (&prev)[48],
                                         uint32_t (&h)[144]) {
  p1_stage<SB0 + 0>(c, j, baddr, cur, prev, h); p1_stage<SB0 + 1>(c, j, baddr, cur, prev, h);
  p1_stage<SB0 + 2>(c, j, baddr, cur, prev, h); p1_stage<SB0 + 3>(c, j, baddr, cur, prev, h);
  p1_stage<SB0 + 4>(c, j, baddr, cur, prev, h); p1_stage<SB0 + 5>(c, j, baddr, cur, prev, h);
  p1_stage<SB0 + 6>(c, j, baddr, cur, prev, h); p1_stage<SB0 + 7>(c, j, baddr, cur, prev, h);
  p1_stage<SB0 + 8>(c, j, baddr, cur, prev, h);
}
template <int S, int I>
__device__ __forceinline__ void p2_one(const MlpCtx& c, float (&cur)[32], uint32_t (&h)[144]) {
  constexpr int kk = 6 * S + I;
  wgmma_rs_n64<(S | I) != 0, ((S * STAGE_BYTES + I * 2048) >> 4)>(cur, h[4 * kk], h[4 * kk + 1], h[4 * kk + 2], h[4 * kk + 3], c.dB);
}
template <int S>
__device__ __forceinline__ void p2_mma(const MlpCtx& c, uint32_t parity, float (&cur)[32], uint32_t (&h)[144]) {
  mbar_wait(c.bars + B_FULL + 8 * S, parity);
  WG_FENCE();
  p2_one<S, 0>(c, cur, h); p2_one<S, 1>(c, cur, h); p2_one<S, 2>(c, cur, h);
  p2_one<S, 3>(c, cur, h); p2_one<S, 4>(c, cur, h); p2_one<S, 5>(c, cur, h);
  WG_COMMIT();
}
__device__ __forceinline__ int chunk_of(int pos, int pr, int rank) {
  const int off = (int)(0x03231201ull >> (4 * pos)) & 3;
  const int mine = (0x168 >> pos) & 1;
  return pos == 1 ? 8 : 2 * ((pr + off) & 3) + (mine ? rank : rank ^ 1);
}
__device__ __forceinline__ void bulk_s2peer(uint32_t rdst, uint32_t src, uint32_t bytes, uint32_t rbar) {
  asm volatile("cp.async.bulk.shared::cluster.shared::cta.mbarrier::complete_tx::bytes [%0], [%1], %2, [%3];"
               ::"r"(rdst), "r"(src), "r"(bytes), "r"(rbar) : "memory");
}
__device__ __forceinline__ void bulk_s2g_release(void* gdst, uint32_t src, uint32_t bytes) {
  asm volatile("cp.async.bulk.global.shared::cta.bulk_group [%0], [%1], %2;\n"
               "cp.async.bulk.commit_group;\ncp.async.bulk.wait_group 0;\nfence.acq_rel.gpu;"
               ::"l"(gdst), "r"(src), "r"(bytes) : "memory");
}
struct Args {
  const __nv_bfloat16 *u, *Are, *Aim, *Bre, *Bim, *Cre, *Cim, *logdt, *Dskip, *gate_w, *w1, *w2, *b1, *b2;
  __nv_bfloat16* out;
};

struct Maps { const CUtensorMap *x, *w1, *xn; };
__device__ __forceinline__ void load_params(uint32_t (&v)[8], const Args& ar, int d, int n) {
  const int idx = d * N_ST + n;
  v[0] = ldg_u16(ar.Are + idx); v[1] = ldg_u16(ar.Aim + idx); v[2] = ldg_u16(ar.Bre + idx); v[3] = ldg_u16(ar.Bim + idx);
  v[4] = ldg_u16(ar.Cre + idx); v[5] = ldg_u16(ar.Cim + idx); v[6] = ldg_u16(ar.logdt + d); v[7] = ldg_u16(ar.Dskip + d);
}
__device__ __forceinline__ uint4 pack_params(uint32_t (&v)[8]) {
  asm volatile("" : "+r"(v[0]), "+r"(v[1]), "+r"(v[2]), "+r"(v[3]), "+r"(v[4]), "+r"(v[5]), "+r"(v[6]), "+r"(v[7])::"memory");
  return make_uint4(v[0] | (v[1] << 16), v[2] | (v[3] << 16), v[4] | (v[5] << 16), v[6] | (v[7] << 16));
}
__device__ __noinline__ uint4 ssm_pass(const Maps tm, char* sm, const int d0, const int pass, const uint4 pv
) {
  const Args& ar = *reinterpret_cast<const Args*>(sm + OFF_ARGS);
  const Scratch& sc = *reinterpret_cast<const Scratch*>(sm + OFF_ARGS + 128);
  const uint32_t sb = smem_u32(sm), bars = sb + OFF_BAR;
  const int tid = threadIdx.x, lane = tid & 31;
  const int warp = __shfl_sync(0xffffffffu, tid >> 5, 0);
  const int bid = blockIdx.x, m = bid >> 3, f = bid & 7;
  const int g = lane >> 2, cc = lane & 3;
  const int ch = warp >> 2, n = tid & 127;
  char* eb = sm + e_off(ch);
  char* lb = sm + l_off(ch);
#define CH_SYNC() asm volatile("bar.sync %0, 128;" ::"r"(ch + 1) : "memory")
  {
    const float are = bf_lo(pv.x), aim = bf_hi(pv.x), bre = bf_lo(pv.y), bim = bf_hi(pv.y);
    const float cre = bf_lo(pv.z), cim = bf_hi(pv.z), ldt = bf_lo(pv.w), dsk = bf_hi(pv.w);
    const float dt = bf_round(expf(ldt));
    const float al = (dt * are) * 1.4426950408889634f, th = dt * aim;
    constexpr float TF32_UNBIAS = 1.0f + 0.7f / 1024.0f;
    const float2 c0 = cmul(make_float2(cre * TF32_UNBIAS, cim * TF32_UNBIAS), make_float2(dt * bre, dt * bim));
    const float2 e64 = cexp_l(al, th, 64.f), e128 = csq(e64), e256 = cexp_l(al, th, 256.f), e512 = csq(e256);
    const float2 k128 = cmul(c0, e128), k256 = cmul(c0, e256), k384 = cmul(k256, e128);
    const float2 k512 = cmul(c0, e512), k516 = cmul(k512, cexp_l(al, th, 4.f));
    const float2 e1024 = cexp_l(al, th, 1024.f), k1024 = cmul(c0, e1024);
    float k2048 = fmaf(k1024.x, e1024.x, -k1024.y * e1024.y) * (1.0f / TF32_UNBIAS);
    char* ca = lb + L_CONST + n * 80;
    SM_F4(ca) = make_float4(al, th, e64.x, e64.y);
    SM_F4(ca + 16) = make_float4(c0.x, c0.y, k128.x, k128.y);
    SM_F4(ca + 32) = make_float4(k256.x, k256.y, k384.x, k384.y);
    SM_F4(ca + 48) = make_float4(k512.x, k512.y, k516.x, k516.y);
    SM_F2(ca + 64) = k1024;
#pragma unroll
    for (int o = 16; o > 0; o >>= 1) k2048 += __shfl_xor_sync(~0u, k2048, o);
    if (lane == 0) SM_F32(lb + L_KC + (warp & 3) * 2576 + 2560) = k2048;
    if (n == 0) SM_F32(lb + L_KB + 8) = dsk;
    __syncwarp();
    DBG_S(0);
    float kd[5][4];
#pragma unroll
    for (int t = 0; t < 5; t++) { kd[t][0] = kd[t][1] = kd[t][2] = kd[t][3] = 0.f; }
    const float l1 = (float)g, l128 = (float)(128 * g);
    const char* cr = lb + L_CONST + ((warp & 3) * 32 + cc) * 80;
    const int o2 = 32 + (g >> 2) * 8, o3 = 48 + (g & 1) * 8, s2 = ((g & 3) << 2) | cc, s3 = ((g >> 1) << 2) | cc;
#pragma unroll 2
    for (int st = 0; st < 8; st++, cr += 320) {
      const float4 q0 = *(const float4*)cr, q1 = *(const float4*)(cr + 16);
      const float2 q2 = *(const float2*)(cr + o2), q3 = *(const float2*)(cr + o3), q4 = *(const float2*)(cr + 64);
      const float2 p1 = cexp_l(q0.x, q0.y, l1), p128 = cexp_l(q0.x, q0.y, l128);
      const float2 p2 = csq(p1), p8 = csq(csq(p2));
      const float2 a1 = cmul(p8, make_float2(q0.z, q0.w));
      float2 x = cmulc(make_float2(q1.x, q1.y), p1);
      mma_tf32(kd[0], p8.x, a1.x, p8.y, a1.y, x.x, x.y);
      x = cmulc(make_float2(q1.z, q1.w), p1);
      mma_tf32(kd[1], p8.x, a1.x, p8.y, a1.y, x.x, x.y);
      x = cmulc(q2, make_float2(__shfl_sync(~0u, p2.x, s2), __shfl_sync(~0u, p2.y, s2)));
      mma_tf32(kd[2], p8.x, a1.x, p8.y, a1.y, x.x, x.y);
      x = cmulc(q3, make_float2(__shfl_sync(~0u, p128.x, s3), __shfl_sync(~0u, p128.y, s3)));
      mma_tf32(kd[3], p8.x, a1.x, p8.y, a1.y, x.x, x.y);
      x = cmulc(q4, p128);
      mma_tf32(kd[4], p8.x, a1.x, p8.y, a1.y, x.x, x.y);
    }
    char* kc = lb + L_KC + (warp & 3) * 2576;
#pragma unroll
    for (int e = 0; e < 2; e++) {
      const int row = g + e * 8;
      SM_F2(kc + 4 * (8 * row + 2 * cc)) = make_float2(kd[0][2 * e], kd[0][2 * e + 1]);
      SM_F2(kc + 4 * (128 + 8 * row + 2 * cc)) = make_float2(kd[1][2 * e], kd[1][2 * e + 1]);
      SM_F2(kc + 4 * (256 + 64 * (cc >> 1) + 4 * row + 2 * (cc & 1))) = make_float2(kd[2][2 * e], kd[2][2 * e + 1]);
      SM_F2(kc + 4 * (384 + 32 * cc + 2 * row)) = make_float2(kd[3][2 * e], kd[3][2 * e + 1]);
      SM_F32(kc + 4 * (512 + 32 * cc + row)) = kd[4][2 * e];
      SM_F32(kc + 4 * (528 + 32 * cc + row)) = kd[4][2 * e + 1];
    }
  }
  DBG_S(1);
  uint32_t lw[9], lg[9];
  ln_load(ar.u, ar.gate_w, (bid & 127) * 16 + warp, lane, lw, lg);
  CH_SYNC();
  {
    const char* kc = lb + L_KC;
    auto kq = [&](int idx) {
      const char* q = kc + 4 * idx;
      return (*(const float*)q + *(const float*)(q + 2576)) + (*(const float*)(q + 5152) + *(const float*)(q + 7728));
    };
#pragma unroll
    for (int it = 0; it < 5; it++) {
      const int idx = n + 128 * it;
      float t = kq(idx);
      if ((it == 1 || it == 2) && n == 127) t -= kq(idx + 1);
      if (it == 4 && n == 0) { SM_F2(lb + L_KB) = make_float2(t, kq(640)); t = 0.f; }
      int off;
      if (it < 2) off = TP_0 + 2 * (272 - idx);
      else if (it == 2) {
        const int sel = n & 3, mu = 32 + (n >> 2);
        off = sel == 2 ? TP_W3B + 2 * (144 - mu) : (sel == 0 ? TP_W3A : sel == 1 ? TP_UA : TP_UB) + 2 * (80 - mu);
      } else if (it == 3) off = ((n & 1) ? TP_W3B : TP_W5) + 2 * (80 - (n >> 1));
      else off = ((n & 1) ? TP_W7 : TP_W9) + 2 * (80 - (n >> 1));
      const unsigned short hv = pack_bf16(t, 0.f);
      SM_U16(eb + E_TAP + off) = hv;
      SM_U16(eb + E_TAP + TP_COPY + off + 2) = hv;
    }
  }
  DBG_S(2);
  if (bid < 128) ln_row(bid * 16 + warp, lane, sc, lw, lg);
  DBG_S(3);
  mbar_wait(bars + B_U, pass & 1);
  {
    const uint32_t src = sb + xg_off(warp >> 1) + ((warp & 1) * 128 + lane) * 16;
    const int mych = g - (d0 & 4);
    char* dst = sm + l_off(mych) + ((warp >> 1) + 1) * 528 + (warp & 1) * 256 + cc * 4;
#pragma unroll
    for (int i = 0; i < 4; i++) {
      uint32_t r[4];
      ldsm4t(r, src + i * 512);
      if (mych >= 0 && mych < 4) {
#pragma unroll
        for (int k = 0; k < 4; k++) SM_U32(dst + i * 64 + k * 16) = r[k];
      }
    }
  }
  __syncthreads();
  DBG_S(4);
  if (bid < 128) {
    if (tid == 480) {
      asm volatile("fence.acq_rel.gpu;" ::: "memory");
      atomicAdd(&sc.flags[256 + m], 1u);
    } else if (tid == 0) {
      asm volatile("cp.async.bulk.prefetch.L2.global [%0], %1;" ::"l"(ar.w1 + (size_t)bid * 20736), "r"(41472) : "memory");
      asm volatile("cp.async.bulk.prefetch.L2.global [%0], %1;" ::"l"(ar.w2 + (size_t)bid * 20736), "r"(41472) : "memory");
    }
  }
#pragma unroll 1
  for (int i = n - 1; i < 224; i += 128) {
    const char* ur = lb + ((i >> 5) + 1) * 528 + (i & 31) * 16;
    const uint4 w0 = *(const uint4*)(ur - ((i & 31) ? 16 : 32) + (i < 0 ? 16 : 0)), w1 = *(const uint4*)ur,
                w2 = *(const uint4*)(ur + ((i & 31) == 31 ? 32 : 16));
    const uint32_t wv[12] = {w0.x, w0.y, w0.z, w0.w, w1.x, w1.y, w1.z, w1.w, w2.x, w2.y, w2.z, w2.w};
    char* o = eb + 32 + 16 * i;
    SM_U4(o + E_UA) = make_uint4(wv[3], wv[4], wv[5], wv[6]);
    SM_U4(o + E_UB) = make_uint4(wv[1], wv[2], wv[3], wv[4]);
    float v[22], wa[16];
#pragma unroll
    for (int k = 1; k < 11; k++) { v[2 * k] = bf_lo(wv[k]); v[2 * k + 1] = bf_hi(wv[k]); }
#pragma unroll
    for (int k = 4; k < 16; k++) wa[k] = (v[k - 1] + v[k]) + v[k + 1];
    SM_U4(o + E_W3A) = make_uint4(pack_bf16(wa[8], wa[9]), pack_bf16(wa[10], wa[11]), pack_bf16(wa[12], wa[13]), pack_bf16(wa[14], wa[15]));
    SM_U4(o + E_W3B) = make_uint4(pack_bf16(wa[4], wa[5]), pack_bf16(wa[6], wa[7]), pack_bf16(wa[8], wa[9]), pack_bf16(wa[10], wa[11]));
    if (i < 192) {
#pragma unroll
      for (int k = 8; k < 16; k++) wa[k] += v[k - 2] + v[k + 2];
      SM_U4(o + E_W5) = make_uint4(pack_bf16(wa[8], wa[9]), pack_bf16(wa[10], wa[11]), pack_bf16(wa[12], wa[13]), pack_bf16(wa[14], wa[15]));
      if (i < 128) {
#pragma unroll
        for (int k = 8; k < 16; k++) wa[k] += v[k - 3] + v[k + 3];
        SM_U4(lb + L_W7 + 32 + 16 * i) =
            make_uint4(pack_bf16(wa[8], wa[9]), pack_bf16(wa[10], wa[11]), pack_bf16(wa[12], wa[13]), pack_bf16(wa[14], wa[15]));
#pragma unroll
        for (int k = 8; k < 16; k++) wa[k] += v[k - 4] + v[k + 4];
        SM_U4(o + E_W9) = make_uint4(pack_bf16(wa[8], wa[9]), pack_bf16(wa[10], wa[11]), pack_bf16(wa[12], wa[13]), pack_bf16(wa[14], wa[15]));
      }
    }
  }
  CH_SYNC();
  DBG_S(5);
  {
    const int role = (warp + ch) & 3;
    uint32_t ea = smem_u32(eb), za = smem_u32(lb);
    asm volatile("" : "+r"(ea), "+r"(za)::"memory");
    const uint32_t tp = ea + E_TAP + ((g & 1) ? TP_COPY + 2 : 0) - 2 * (g - 2 * cc);
    if (role < 2) {
      uint32_t ta[17][4];
      load_tquads<0, 17, TP_0 + 544>(ta, tp);
      float acc[8][4];
#pragma unroll
      for (int i = 0; i < 8; i++) { acc[i][0] = acc[i][1] = acc[i][2] = acc[i][3] = 0.f; }
      const uint32_t bpos = za + ((lane & 7) + 1) * 528 + role * 256 + (lane >> 3) * 16;
      const uint32_t bmid = role ? bpos : bpos - 16;
#pragma unroll
      for (int j2 = -16; j2 < 8; j2 += 2) {
        uint32_t b[4];
        ldsm4_free(b, (j2 < -8 ? bpos - 16 : j2 < 0 ? bmid : bpos) + 32 * j2);
#pragma unroll
        for (int hf = 0; hf < 2; hf++) {
#pragma unroll
          for (int i = 0; i < 8; i++) {
            const int k = i - j2 - hf;
            if (k >= 0 && k <= 16) mma_bf16(acc[i], ta[k][0], ta[k][1], ta[k][2], ta[k][3], b[2 * hf], b[2 * hf + 1]);
          }
        }
      }
      char* ya = lb + L_Y + 4 * (520 * cc + 128 * role + g);
#pragma unroll
      for (int i = 0; i < 8; i++) {
        SM_F32(ya + 64 * i) = acc[i][0]; SM_F32(ya + 64 * i + 1040) = acc[i][1];
        SM_F32(ya + 64 * i + 32) = acc[i][2]; SM_F32(ya + 64 * i + 1072) = acc[i][3];
      }
    } else if (role == 2) {
      p8_tiles<1, 11>(ea, za, lb, tp, lane);
    } else {
      p8_tiles<11, 16>(ea, za, lb, tp, lane);
      float acc[2][5][4];
#pragma unroll
      for (int i = 0; i < 10; i++) { acc[i / 5][i % 5][0] = acc[i / 5][i % 5][1] = acc[i / 5][i % 5][2] = acc[i / 5][i % 5][3] = 0.f; }
#pragma unroll
      for (int sg = 0; sg < 2; sg++) {
        uint32_t tq[5][4];
        if (sg == 0) load_tquads<4, 9, TP_W9 + 288>(tq, tp); else load_tquads<4, 9, TP_W7 + 288>(tq, tp);
        const uint32_t sa = (sg == 0 ? ea + E_W9 : za + L_W7 - 16) + 32 + (lane & 15) * 32 + (lane >> 4) * 16;
#pragma unroll
        for (int J = -1 + sg; J < 4; J++) {
          uint32_t b[4];
          ldsm4t_free(b, (J < 0 && (lane & 15) < 15) ? za : sa + J * 512);
#pragma unroll
          for (int k = 4; k < 9; k++) {
            const int I = J + k;
            if (I < 8) {
              mma_bf16(acc[0][I - 3], tq[k - 4][0], tq[k - 4][1], tq[k - 4][2], tq[k - 4][3], b[0], b[1]);
              mma_bf16(acc[1][I - 3], tq[k - 4][0], tq[k - 4][1], tq[k - 4][2], tq[k - 4][3], b[2], b[3]);
            }
          }
        }
      }
      char* a = lb + L_Y + 2 * L_YB + 4 * (16 * g + 2 * cc);
#pragma unroll
      for (int hh = 0; hh < 2; hh++) {
#pragma unroll
        for (int I = 3; I < 8; I++) {
          SM_F2(a + 32 * hh + 1040 * (I - 3)) = make_float2(acc[hh][I - 3][0], acc[hh][I - 3][1]);
          SM_F2(a + 32 * hh + 1040 * (I - 3) + 512) = make_float2(acc[hh][I - 3][2], acc[hh][I - 3][3]);
        }
      }
    }
  }
  __syncthreads();
  DBG_S(6);
  if (lane == 0) {
    HFENCE();
    if (bid >= 128) {
      if (pass < 3 && (warp & 1) == 0) {
        mbar_expect_tx(bars + B_U, 4096);
        tma2d(sb + xg_off(warp >> 1), tm.x, (d0 + 4) & ~7, (warp >> 1) * 256, bars + B_U);
      }
    } else if (warp < 6) {
      mbar_expect_tx(bars + B_FULL + 8 * warp, STAGE_BYTES);
      tma3d(sb + OFF_ST + warp * STAGE_BYTES, tm.w1, 0, warp * 64, f * 18, bars + B_FULL + 8 * warp);
    } else if (warp < 8) {
      wait_flag(&sc.flags[256 + m], 8);
      mbar_expect_tx(bars + B_X + 8 * (warp - 6), 16384);
      tma2d(sb + (warp - 6) * 16384, tm.xn, (warp - 6) * 64, m * 128, bars + B_X + 8 * (warp - 6));
    }
  }
  __syncwarp();
  uint32_t pnext[8];
#pragma unroll
  for (int i = 0; i < 8; i++) pnext[i] = 0;
  if (bid >= 128 && pass < 3) load_params(pnext, ar, d0 + 4 + ch, n);
  {
    const float4 kb = SM_F4(lb + L_KB);
    const uint32_t dk = pack_bf16(kb.z, kb.z);
#pragma unroll
    for (int k = 0; k < 4; k++) {
      const int t0 = n * 4 + 512 * k;
      char* ya = lb + L_Y + 4 * (t0 + 4 * (t0 >> 8));
      float4 y = SM_F4(ya);
      if (k > 0 || t0 >= 128) { const float4 b = SM_F4(ya + L_YB); y.x += b.x; y.y += b.y; y.z += b.z; y.w += b.w; }
      if (k > 1 || (k == 1 && t0 >= 768)) {
        const float4 b = SM_F4(ya + 2 * L_YB - 3120);
        y.x += b.x; y.y += b.y; y.z += b.z; y.w += b.w;
        if (k > 1 || t0 >= 1020) {
          const char* wp = lb + L_W7 + 32 + 2 * (t0 - 1026);
          const uint32_t wl = *(const uint32_t*)wp, wm = *(const uint32_t*)(wp + 4), wh = *(const uint32_t*)(wp + 8);
          y.x = fmaf(kb.x, bf_hi(wl), y.x); y.y = fmaf(kb.x, bf_lo(wm), y.y);
          y.z = fmaf(kb.x, bf_hi(wm), y.z); y.w = fmaf(kb.x, bf_lo(wh), y.w);
          if (k == 3 && n == 127) {
            const uint2 u03 = SM_U2(lb + 528);
            float pre = bf_lo(u03.x);
            y.x = fmaf(kb.y, pre, y.x); pre += bf_hi(u03.x);
            y.y = fmaf(kb.y, pre, y.y); pre += bf_lo(u03.y);
            y.z = fmaf(kb.y, pre, y.z); pre += bf_hi(u03.y);
            y.w = fmaf(kb.y, pre, y.w);
          }
        }
      }
      const uint2 uu = SM_U2(lb + ((t0 >> 8) + 1) * 528 + (t0 & 255) * 2);
      uint2 o;
      o.x = bf2_add(pack_bf16(y.x, y.y), bf2_mul(uu.x, dk));
      o.y = bf2_add(pack_bf16(y.z, y.w), bf2_mul(uu.y, dk));
      *reinterpret_cast<uint2*>(sc.aT + (size_t)(d0 + ch) * L_SEQ + t0) = o;
    }
  }
  __syncthreads();
  DBG_S(7);
  return pack_params(pnext);
}

__global__ void __cluster_dims__(2, 1, 1) __launch_bounds__(512, 1)
fused_kernel(const __grid_constant__ CUtensorMap tm_x, const __grid_constant__ CUtensorMap tm_w1,
             const __grid_constant__ CUtensorMap tm_w2, const __grid_constant__ CUtensorMap tm_aT,
             const __grid_constant__ CUtensorMap tm_xn, const __grid_constant__ CUtensorMap tm_out,
             const __grid_constant__ CUtensorMap tm_a8,
             const __grid_constant__ Args ar, const __grid_constant__ Scratch sc) {
  extern __shared__ __align__(1024) char smem_raw[];
  DBG_G(28);
  const uint32_t sb = (smem_u32(smem_raw) + 1023) & ~1023u;
  char* sm = smem_raw + (sb - smem_u32(smem_raw));
  const uint32_t bars = sb + OFF_BAR;
  const int tid = threadIdx.x, lane = tid & 31;
  const int warp = __shfl_sync(0xffffffffu, tid >> 5, 0), wg = warp >> 2;
  const int bid = blockIdx.x;
  const int m = bid >> 3, f = bid & 7, rank = f & 1, pr = f >> 1;

  const int dbase = bid < 128 ? bid * 4 : 512 + (bid - 128) * 16;
  uint32_t praw[8];
  load_params(praw, ar, dbase + wg, tid & 127);

  if (lane == 0) {
    if (warp == 8) {
#pragma unroll
      for (int i = 0; i < B_EMPTY / 8; i++) mbar_init(bars + i * 8, 1);
      asm volatile("fence.mbarrier_init.release.cluster;" ::: "memory");
#pragma unroll
      for (int i = 0; i < 4; i++) mbar_expect_tx(bars + B_RB + 8 * i, 16384);
    } else if (warp == 9) {
#pragma unroll
      for (int i = B_EMPTY / 8; i < NBARS; i++) mbar_init(bars + i * 8, 8);
      asm volatile("fence.mbarrier_init.release.cluster;" ::: "memory");
    } else if (warp == 10) {
      asm volatile("prefetch.tensormap [%0];" ::"l"(&tm_x) : "memory");
    } else if (warp == 11) {
      *reinterpret_cast<Args*>(sm + OFF_ARGS) = ar;
      *reinterpret_cast<Scratch*>(sm + OFF_ARGS + 128) = sc;
    }
  }
  __syncthreads();
  asm volatile("barrier.cluster.arrive.relaxed.aligned;" ::: "memory");

  {
    Maps tm;
    tm.x = &tm_x; tm.w1 = &tm_w1; tm.xn = &tm_xn;
    const int npass = bid < 128 ? 1 : 4;
    if (lane == 0 && (warp & 1) == 0) {
      mbar_expect_tx(bars + B_U, 4096);
      tma2d(sb + xg_off(warp >> 1), &tm_x, dbase & ~7, (warp >> 1) * 256, bars + B_U);
    }
    {
      char* eb = sm + e_off(wg);
      const int n = tid & 127;
      const uint4 z = make_uint4(0, 0, 0, 0);
      SM_U4(eb + E_TAP + n * 16) = z;
      if (n < 104) SM_U4(eb + E_TAP + 2048 + n * 16) = z;
      else if (n == 104) SM_U4(eb + E_W9) = z;
      if (n < 33) SM_U4(sm + l_off(wg) + n * 16) = z;
    }
    uint4 pv = pack_params(praw);
#pragma unroll 1
    for (int pass = 0; pass < npass; pass++)
      pv = ssm_pass(tm, sm, dbase + pass * 4, pass, pv
      );
  }
  if (bid >= 128) {
    if (tid == 0) {
      asm volatile("fence.acq_rel.gpu;" ::: "memory");
      atomicAdd(&sc.flags[304], 1u);
    }
    __syncwarp();
    asm volatile("barrier.cluster.wait.acquire.aligned;" ::: "memory");
    return;
  }

  const uint32_t rdelta = mapa(sb, rank ^ 1) - sb;
  if (wg >= 2) {
    asm volatile("setmaxnreg.dec.sync.aligned.u32 24;");
    asm volatile("barrier.cluster.wait.acquire.aligned;" ::: "memory");
    const int pw = warp - 8;
    if (lane == 0) {
      if (pw < 2) {
        int slot = pw, par = 0;
#pragma unroll 1
        for (int it = 6 + pw; it < 54; it += 2) {
          const int ch = it / 9, s = it - ch * 9;
          const uint32_t fb = bars + B_FULL + 8 * slot;
          mbar_wait(bars + B_EMPTY + 8 * slot, par);
          mbar_expect_tx(fb, STAGE_BYTES);
          tma3d(sb + OFF_ST + slot * STAGE_BYTES, &tm_w1, 0, s * 64, f * 18 + ch * 3, fb);
          slot += 2;
          if (slot >= 6) { slot -= 6; par ^= 1; }
        }
#pragma unroll 1
        for (int pos = 0; pos < 9; pos++) {
          const int chunk = chunk_of(pos, pr, rank);
#pragma unroll 1
          for (slot = pw; slot < 6; slot += 2) {
            const uint32_t fb = bars + B_FULL + 8 * slot;
            mbar_wait(bars + B_EMPTY + 8 * slot, par);
            mbar_expect_tx(fb, STAGE_BYTES);
            tma2d(sb + OFF_ST + slot * STAGE_BYTES, &tm_w2, chunk * 64, f * 576 + slot * 96, fb);
          }
          par ^= 1;
        }
        if (pw == 0) {
          wait_flag(&sc.flags[288 + f * 2], 16);
          mbar_wait(bars + B_EMPTY, par);
          mbar_wait(bars + B_EMPTY + 8, par);
          mbar_expect_tx(bars + B_FULL, 16384);
          tma2d(sb + OFF_ST, &tm_aT, m * 128, f * 64, bars + B_FULL);
          tma2d(sb + OFF_ST + 8192, &tm_aT, m * 128 + 64, f * 64, bars + B_FULL);
          if (atomicAdd(&sc.flags[289 + f * 2], 1u) == 15) { sc.flags[288 + f * 2] = 0; sc.flags[289 + f * 2] = 0; }
        }
      } else if (pw == 2) {
        mbar_wait(bars + B_P1R, 0);
#pragma unroll 1
        for (int k = 0; k < 4; k++) {
          mbar_wait(bars + B_TS + 8 * k, 0);
          HFENCE();
          bulk_s2peer(sb + k * 16384 + rdelta, sb + OFF_STG + k * 16384, 16384, bars + B_RB + 8 * k + rdelta);
        }
#pragma unroll 1
        for (int k = 0; k < 4; k++) mbar_wait(bars + B_RB + 8 * k, 0);
        mbar_arrive_remote(bars + B_FIN + rdelta);
        mbar_wait(bars + B_FIN, 0);
      } else if (pw == 3) {
        mbar_wait(bars + B_TS8, 0);
        HFENCE();
        bulk_s2g_release(sc.slots8 + (size_t)(m * 8 + f) * 4096, sb + OFF_C8, 16384);
#pragma unroll 1
        for (int i = 0; i < 8; i++) atomicAdd(&sc.flags[m * 16 + 8 + i], 1u);
#pragma unroll 1
        for (int k = 0; k < 3; k++) {
          const int chunk = 2 * ((pr + k + 1) & 3) + rank;
          mbar_wait(bars + B_TR + 8 * k, 0);
          HFENCE();
          bulk_s2g_release(sc.slots + (size_t)((m * 8 + chunk) * 3 + k) * 4096, sb + k * 16384, 16384);
          atomicAdd(&sc.flags[m * 16 + chunk], 1u);
          DBG_H(16 + k);
          if (k == 0) {
            mbar_expect_tx(bars + B_OWN, 65536);
            wait_flag(&sc.flags[m * 16 + 8 + f], 8);
            sc.flags[m * 16 + 8 + f] = 0;
#pragma unroll 1
            for (int i = 0; i < 8; i++)
              bulk_g2s(sb + OFF_C8 + i * 2048, sc.slots8 + (size_t)(m * 8 + i) * 4096 + f * 512, 2048, bars + B_OWN);
          }
        }
        wait_flag(&sc.flags[m * 16 + f], 3);
        sc.flags[m * 16 + f] = 0;
        bulk_g2s(sb, sc.slots + (size_t)((m * 8 + f) * 3) * 4096, 49152, bars + B_OWN);
        if (f == 0) sc.flags[256 + m] = 0;
        DBG_H(19);
      } else if (pw == 4) {
        asm volatile("fence.acq_rel.gpu;" ::: "memory");
        atomicAdd(&sc.flags[288 + (bid >> 4) * 2], 1u);
        mbar_wait(bars + B_TR + 8, 0);
        wait_flag(&sc.flags[304], 4);
        mbar_expect_tx(bars + B_A8, 2048);
        tma2d(sb + OFF_A8, &tm_a8, m * 128, 512 + f * 8, bars + B_A8);
        if (atomicAdd(&sc.flags[305], 1u) == 127) { sc.flags[304] = 0; sc.flags[305] = 0; }
      } else {
        HFENCE();
#pragma unroll 1
        for (int kb = pw - 3; kb < 9; kb += 3) {
          mbar_expect_tx(bars + B_X + 8 * kb, kb == 8 ? 16384 + 2304 : 16384);
          tma2d(sb + kb * 16384, &tm_xn, kb * 64, m * 128, bars + B_X + 8 * kb);
          if (kb == 8) {
            bulk_g2s(sb + OFF_B1, ar.b1 + f * 576, 1152, bars + B_X + 64);
            bulk_g2s(sb + OFF_B2, ar.b2, 1152, bars + B_X + 64);
          }
        }
      }
    }
  } else {
    asm volatile("setmaxnreg.inc.sync.aligned.u32 232;");
    const int wi = warp & 3;
    DBG_T(0);
    MlpCtx c;
    c.bars = bars; c.lane = lane;
    c.dA = (((sb + wg * 8192) & 0x3FFFF) >> 4) | (1u << 16);
    c.dB = ((sb + OFF_ST) & 0x3FFFF) >> 4;

    uint32_t h[144];
    float acc2a[32], acc2b[32];
    {
      float accA[48], accB[48];
#pragma unroll
      for (int i = 0; i < 48; i++) { accA[i] = 0.f; accB[i] = 0.f; }
#pragma unroll
      for (int i = 0; i < 144; i++) h[i] = 0;
      uint32_t baddr = sb + OFF_B1 + (lane & 3) * 4 - 192;
#pragma unroll 1
      for (int j = 0; j < 3; j++) {
        DBG_T(11 + 2 * j);
        p1_chunk<0>(c, j, baddr, accA, accB, h);
        baddr += 192;
        DBG_T(10 + 2 * j);
        p1_chunk<9>(c, j, baddr, accB, accA, h);
        baddr += 192;
      }
      DBG_T(2);
      p2_mma<0>(c, 1, acc2a, h);
      wg_wait<1>();
      stage_release(c, 5);
      fence_regs(accB);
      asm volatile("barrier.cluster.wait.acquire.aligned;" ::: "memory");
      if (lane == 0) { mbar_arrive(bars + B_P1L); mbar_arrive_remote(bars + B_P1R + rdelta); }
      p2_mma<1>(c, 1, acc2a, h);
      gelu_part<0>(baddr, accB); gelu_part<1>(baddr, accB);
      wg_wait<1>(); stage_release(c, 0);
      p2_mma<2>(c, 1, acc2a, h);
      gelu_part<2>(baddr, accB); gelu_part<3>(baddr, accB);
      wg_wait<1>(); stage_release(c, 1);
      p2_mma<3>(c, 1, acc2a, h);
      gelu_part<4>(baddr, accB);
      wg_wait<1>(); stage_release(c, 2);
      p2_mma<4>(c, 1, acc2a, h);
      gelu_part<5>(baddr, accB);
#pragma unroll
      for (int i = 0; i < 24; i++) h[120 + i] = __float_as_uint(accB[(i >> 2) * 8 + (i & 3)]);
      wg_wait<1>(); stage_release(c, 3);
      p2_mma<5>(c, 1, acc2a, h);
      wg_wait<1>(); stage_release(c, 4);
    }
    const uint32_t lbuf = sb + warp * 2048 + lane * 16;
    mbar_wait(bars + B_P1L, 0);
#pragma unroll 1
    for (int pos = 0; pos < 8; pos++) {
      const bool recv = (0x68 >> pos) & 1;
      const int k = recv ? (pos - 2) >> 1 : (pos + 1) >> 1;
      const int ks = k > 3 ? 3 : k;
      const uint32_t addr = lbuf + ks * 16384 + (recv ? 0 : OFF_STG);
      const uint32_t sig = bars + (recv ? B_TR + 8 * k : pos == 1 ? B_TS8 : B_TS + 8 * ks);
      if (recv) mbar_wait(bars + B_RB + k * 8, 0);
      wg_wait<0>(); stage_release(c, 5);
      fence_regs(acc2a);
      DBG_T(20 + pos);
      if (recv) {
#pragma unroll
        for (int i = 0; i < 4; i++) {
          const float4 r = lds128f(addr + i * 512);
          const uint32_t w0 = __float_as_uint(r.x), w1 = __float_as_uint(r.y), w2 = __float_as_uint(r.z), w3 = __float_as_uint(r.w);
          acc2a[8 * i + 0] += bf_lo(w0); acc2a[8 * i + 1] += bf_hi(w0); acc2a[8 * i + 2] += bf_lo(w1); acc2a[8 * i + 3] += bf_hi(w1);
          acc2a[8 * i + 4] += bf_lo(w2); acc2a[8 * i + 5] += bf_hi(w2); acc2a[8 * i + 6] += bf_lo(w3); acc2a[8 * i + 7] += bf_hi(w3);
        }
      }
      if (pos == 1) {
        const uint32_t a8 = sb + OFF_C8 + warp * 256 + lane * 8;
#pragma unroll
        for (int q = 0; q < 8; q++)
          asm volatile("st.shared.v2.u32 [%0], {%1,%2};" ::"r"(a8 + q * 2048), "r"(pack_bf16(acc2a[4 * q], acc2a[4 * q + 1])),
                       "r"(pack_bf16(acc2a[4 * q + 2], acc2a[4 * q + 3])) : "memory");
      } else {
#pragma unroll
        for (int i = 0; i < 4; i++)
          sts128(addr + i * 512, pack_bf16(acc2a[8 * i], acc2a[8 * i + 1]), pack_bf16(acc2a[8 * i + 2], acc2a[8 * i + 3]),
                 pack_bf16(acc2a[8 * i + 4], acc2a[8 * i + 5]), pack_bf16(acc2a[8 * i + 6], acc2a[8 * i + 7]));
      }
      const uint32_t par = pos & 1;
      p2_mma<0>(c, par, acc2a, h);
      __syncwarp();
      if (lane == 0) mbar_arrive(sig);
      p2_mma<1>(c, par, acc2a, h);
      wg_wait<1>(); stage_release(c, 0);
      p2_mma<2>(c, par, acc2a, h);
      wg_wait<1>(); stage_release(c, 1);
      p2_mma<3>(c, par, acc2a, h);
      wg_wait<1>(); stage_release(c, 2);
      p2_mma<4>(c, par, acc2a, h);
      wg_wait<1>(); stage_release(c, 3);
      p2_mma<5>(c, par, acc2a, h);
      wg_wait<1>(); stage_release(c, 4);
    }
    DBG_T(3);
    {
      const int g = lane >> 2, cc = lane & 3;
      const int t0 = m * 128 + warp * 16 + g;
      const uint2 ga = __ldcg(&sc.gate[t0]), gb = __ldcg(&sc.gate[t0 + 8]);
#pragma unroll
      for (int i = 0; i < 32; i++) acc2b[i] = 0.f;
      mbar_wait(bars + B_RB + 24, 0);
      mbar_wait(bars + B_OWN, 0);
      DBG_T(8);
#pragma unroll
      for (int k = 0; k < 4; k++) {
#pragma unroll
        for (int i = 0; i < 4; i++) {
          float4 r = lds128f(lbuf + k * 16384 + i * 512);
          const uint32_t w0 = __float_as_uint(r.x), w1 = __float_as_uint(r.y), w2 = __float_as_uint(r.z), w3 = __float_as_uint(r.w);
          acc2b[8 * i + 0] += bf_lo(w0); acc2b[8 * i + 1] += bf_hi(w0); acc2b[8 * i + 2] += bf_lo(w1); acc2b[8 * i + 3] += bf_hi(w1);
          acc2b[8 * i + 4] += bf_lo(w2); acc2b[8 * i + 5] += bf_hi(w2); acc2b[8 * i + 6] += bf_lo(w3); acc2b[8 * i + 7] += bf_hi(w3);
        }
      }
      float c8[4] = {0.f, 0.f, 0.f, 0.f};
#pragma unroll
      for (int i = 0; i < 8; i++) {
        uint32_t w0, w1;
        asm volatile("ld.shared.v2.u32 {%0,%1}, [%2];" : "=r"(w0), "=r"(w1) : "r"(sb + OFF_C8 + i * 2048 + warp * 256 + lane * 8));
        c8[0] += bf_lo(w0); c8[1] += bf_hi(w0); c8[2] += bf_lo(w1); c8[3] += bf_hi(w1);
      }
      DBG_T(9);
      mbar_wait(bars + B_FULL, 0);
      wg_wait<0>();
      fence_regs(acc2a);
      DBG_T(4);
#pragma unroll
      for (int jj = 0; jj < 4; jj++) {
        uint32_t a[4];
        {
          const int dl = 8 * (2 * jj + (lane >> 4)) + (lane & 7);
          const int chk = 2 * wi + ((lane >> 3) & 1);
          ldsm4t(a, sb + OFF_ST + wg * 8192 + dl * 128 + ((chk ^ (dl & 7)) << 4));
        }
        uint32_t o[4];
#pragma unroll
        for (int e = 0; e < 2; e++) {
          const int q = 2 * jj + e;
          uint32_t bb = lds32(sb + OFF_B2 + (f * 64 + q * 8 + cc * 2) * 2);
          uint32_t v0 = bf2_add(pack_bf16(acc2a[4 * q] + acc2b[4 * q], acc2a[4 * q + 1] + acc2b[4 * q + 1]), bb);
          uint32_t v1 = bf2_add(pack_bf16(acc2a[4 * q + 2] + acc2b[4 * q + 2], acc2a[4 * q + 3] + acc2b[4 * q + 3]), bb);
          o[2 * e] = bf2_add(bf2_mul(ga.x, a[2 * e]), bf2_mul(ga.y, v0));
          o[2 * e + 1] = bf2_add(bf2_mul(gb.x, a[2 * e + 1]), bf2_mul(gb.y, v1));
        }
        {
          const int row = (lane & 7) + ((lane >> 3) & 1) * 8;
          const uint32_t addr = sb + 49152 + warp * 2048 + row * 128 + (((2 * jj + (lane >> 4)) ^ (row & 7)) << 4);
          asm volatile("stmatrix.sync.aligned.m8n8.x4.shared.b16 [%0], {%1,%2,%3,%4};"
                       ::"r"(addr), "r"(o[0]), "r"(o[1]), "r"(o[2]), "r"(o[3]) : "memory");
        }
      }
      asm volatile("fence.proxy.async.shared::cta;" ::: "memory");
      __syncwarp();
      if (lane == 0) {
        asm volatile("cp.async.bulk.tensor.2d.global.shared::cta.bulk_group [%0, {%2, %3}], [%1];\n"
                     "cp.async.bulk.commit_group;"
                     ::"l"(&tm_out), "r"(sb + 49152 + warp * 2048), "r"(f * 64), "r"(m * 128 + warp * 16) : "memory");
      }
      __syncwarp();
      mbar_wait(bars + B_A8, 0);
      {
        __nv_bfloat16* op = ar.out + (size_t)t0 * D_MOD + cc * 2 + 512 + f * 8;
        uint32_t a0, a1;
        const uint32_t addr = sb + OFF_A8 + (lane & 7) * 256 + (warp * 2 + ((lane >> 3) & 1)) * 16;
        asm volatile("ldmatrix.sync.aligned.m8n8.x2.trans.shared.b16 {%0,%1}, [%2];" : "=r"(a0), "=r"(a1) : "r"(addr));
        const uint32_t bb = lds32(sb + OFF_B2 + (512 + f * 8 + cc * 2) * 2);
        const uint32_t v0 = bf2_add(pack_bf16(c8[0], c8[1]), bb), v1 = bf2_add(pack_bf16(c8[2], c8[3]), bb);
        *reinterpret_cast<uint32_t*>(op) = bf2_add(bf2_mul(ga.x, a0), bf2_mul(ga.y, v0));
        *reinterpret_cast<uint32_t*>(op + 8 * D_MOD) = bf2_add(bf2_mul(gb.x, a1), bf2_mul(gb.y, v1));
      }
      if (lane == 0) asm volatile("cp.async.bulk.wait_group.read 0;" ::: "memory");
      DBG_T(5);
      DBG_G(29);
    }
  }
}

typedef CUresult (*EncodeTiledFn)(CUtensorMap*, CUtensorMapDataType, cuuint32_t, void*, const cuuint64_t*,
                                  const cuuint64_t*, const cuuint32_t*, const cuuint32_t*, CUtensorMapInterleave,
                                  CUtensorMapSwizzle, CUtensorMapL2promotion, CUtensorMapFloatOOBfill);

static void make_map(EncodeTiledFn enc, CUtensorMap* tm, const void* base, uint64_t inner, uint64_t outer, uint32_t binner,
                     uint32_t bouter, CUtensorMapSwizzle swz) {
  cuuint64_t gd[2] = {inner, outer};
  cuuint64_t gs[1] = {inner * 2};
  cuuint32_t bd[2] = {binner, bouter};
  cuuint32_t es[2] = {1, 1};
  enc(tm, CU_TENSOR_MAP_DATA_TYPE_BFLOAT16, 2, const_cast<void*>(base), gd, gs, bd, es, CU_TENSOR_MAP_INTERLEAVE_NONE, swz,
      CU_TENSOR_MAP_L2_PROMOTION_L2_128B, CU_TENSOR_MAP_FLOAT_OOB_FILL_NONE);
}

extern "C" void kernel_launch(void* const* d_in, const int* in_sizes, int n_in, void* d_out, int out_size) {
  typedef const __nv_bfloat16* BP;
  Args ar;
  ar.u = (BP)d_in[0]; ar.Are = (BP)d_in[1]; ar.Aim = (BP)d_in[2]; ar.Bre = (BP)d_in[3]; ar.Bim = (BP)d_in[4];
  ar.Cre = (BP)d_in[5]; ar.Cim = (BP)d_in[6]; ar.logdt = (BP)d_in[7]; ar.Dskip = (BP)d_in[8];
  ar.w1 = (BP)d_in[10]; ar.b1 = (BP)d_in[11]; ar.w2 = (BP)d_in[12]; ar.b2 = (BP)d_in[13]; ar.gate_w = (BP)d_in[14];
  ar.out = (__nv_bfloat16*)d_out;

  static EncodeTiledFn enc = nullptr;
  static Scratch sc;
  if (!enc) {
    cudaDriverEntryPointQueryResult qr;
    cudaGetDriverEntryPoint("cuTensorMapEncodeTiled", (void**)&enc, cudaEnableDefault, &qr);
    cudaGetSymbolAddress((void**)&sc.aT, g_aT);
    cudaGetSymbolAddress((void**)&sc.xn, g_xn);
    cudaGetSymbolAddress((void**)&sc.gate, g_gate);
    cudaGetSymbolAddress((void**)&sc.slots, g_slots);
    cudaGetSymbolAddress((void**)&sc.slots8, g_slots8);
    cudaGetSymbolAddress((void**)&sc.flags, g_flags);
    sc.dbg = nullptr;
    cudaFuncSetAttribute(fused_kernel, cudaFuncAttributeMaxDynamicSharedMemorySize, SMEM_BYTES);
  }
  CUtensorMap tm_x, tm_w1, tm_w2, tm_aT, tm_xn, tm_out, tm_a8;
  make_map(enc, &tm_a8, sc.aT, L_SEQ, D_MOD, 128, 8, CU_TENSOR_MAP_SWIZZLE_NONE);
  make_map(enc, &tm_x, ar.u, D_MOD, L_SEQ, 8, 256, CU_TENSOR_MAP_SWIZZLE_NONE);
  make_map(enc, &tm_w2, ar.w2, D_MOD, F_HID, 64, 96, CU_TENSOR_MAP_SWIZZLE_128B);
  make_map(enc, &tm_aT, sc.aT, L_SEQ, D_MOD, 64, 64, CU_TENSOR_MAP_SWIZZLE_128B);
  make_map(enc, &tm_xn, sc.xn, D_MOD, L_SEQ, 64, 128, CU_TENSOR_MAP_SWIZZLE_128B);
  make_map(enc, &tm_out, d_out, D_MOD, L_SEQ, 64, 16, CU_TENSOR_MAP_SWIZZLE_128B);
  {
    cuuint64_t gd[3] = {32, D_MOD, F_HID / 32};
    cuuint64_t gs[2] = {F_HID * 2, 64};
    cuuint32_t bd[3] = {32, 64, 3};
    cuuint32_t es[3] = {1, 1, 1};
    enc(&tm_w1, CU_TENSOR_MAP_DATA_TYPE_BFLOAT16, 3, (void*)ar.w1, gd, gs, bd, es, CU_TENSOR_MAP_INTERLEAVE_NONE,
        CU_TENSOR_MAP_SWIZZLE_64B, CU_TENSOR_MAP_L2_PROMOTION_L2_128B, CU_TENSOR_MAP_FLOAT_OOB_FILL_NONE);
  }
  fused_kernel<<<132, 512, SMEM_BYTES, cudaStreamPerThread>>>(tm_x, tm_w1, tm_w2, tm_aT, tm_xn, tm_out, tm_a8, ar, sc);
}
```

```cpp
#include <cuda_runtime.h>
#include <cuda_bf16.h>
#include <cuda.h>
#include <stdint.h>

#define HFENCE() asm volatile("fence.proxy.async.shared::cta;" ::: "memory")
#define L_SEQ 2048
#define D_MOD 576
#define F_HID 4608
#define N_ST 128

__device__ __align__(1024) __nv_bfloat16 g_aT[D_MOD * L_SEQ];
__device__ __align__(1024) __nv_bfloat16 g_xn[L_SEQ * D_MOD];
__device__ __align__(1024) uint32_t g_slots[16 * 8 * 3 * 4096];
__device__ __align__(1024) uint32_t g_slots8[16 * 8 * 4096];
__device__ uint2 g_gate[L_SEQ];
__device__ unsigned int g_flags[832];
struct Scratch {
  __nv_bfloat16* aT; __nv_bfloat16* xn; uint2* gate; uint32_t* slots; uint32_t* slots8; unsigned int* flags;
  long long* dbg;
};
#define DBG_T(i)
#define DBG_S(i)
#define DBG_H(i)
#define DBG_G(i)

__device__ __forceinline__ uint32_t smem_u32(const void* p) { return (uint32_t)__cvta_generic_to_shared(p); }
__device__ __forceinline__ void mbar_init(uint32_t bar, int cnt) {
  asm volatile("mbarrier.init.shared::cta.b64 [%0], %1;" ::"r"(bar), "r"(cnt));
}
__device__ __forceinline__ void mbar_expect_tx(uint32_t bar, uint32_t bytes) {
  asm volatile("mbarrier.arrive.expect_tx.shared::cta.b64 _, [%0], %1;" ::"r"(bar), "r"(bytes) : "memory");
}
__device__ __forceinline__ void mbar_arrive(uint32_t bar) {
  asm volatile("mbarrier.arrive.shared::cta.b64 _, [%0];" ::"r"(bar) : "memory");
}
__device__ __forceinline__ void mbar_arrive_remote(uint32_t remote_bar) {
  asm volatile("mbarrier.arrive.relaxed.cluster.shared::cluster.b64 _, [%0];" ::"r"(remote_bar) : "memory");
}
__device__ __forceinline__ void mbar_wait(uint32_t bar, uint32_t parity) {
  asm volatile(
      "{\n.reg .pred p;\n.reg .u32 n;\nmov.u32 n, 0;\n"
      "W_%=:\nmbarrier.try_wait.parity.shared::cta.b64 p, [%0], %1;\n@p bra D_%=;\n"
      "add.u32 n, n, 1;\nsetp.lt.u32 p, n, 400000;\n@p bra W_%=;\ntrap;\nD_%=:\n}"
      ::"r"(bar), "r"(parity) : "memory");
}
__device__ __forceinline__ void tma2d(uint32_t dst, const CUtensorMap* tm, int c0, int c1, uint32_t bar) {
  asm volatile("cp.async.bulk.tensor.2d.shared::cluster.global.mbarrier::complete_tx::bytes [%0], [%1, {%3, %4}], [%2];"
               ::"r"(dst), "l"(tm), "r"(bar), "r"(c0), "r"(c1) : "memory");
}
__device__ __forceinline__ void wait_flag(unsigned int* flag, unsigned int target) {
  asm volatile(
      "{\n.reg .pred p;\n.reg .u32 n, v;\nmov.u32 n, 0;\n"
      "W_%=:\nld.acquire.gpu.global.u32 v, [%0];\nsetp.ge.u32 p, v, %1;\n@p bra D_%=;\n"
      "nanosleep.u32 32;\nadd.u32 n, n, 1;\nsetp.lt.u32 p, n, 4000000;\n@p bra W_%=;\ntrap;\nD_%=:\n}"
      ::"l"(flag), "r"(target) : "memory");
}
__device__ __forceinline__ void bulk_g2s(uint32_t dst, const void* src, uint32_t bytes, uint32_t bar) {
  asm volatile("cp.async.bulk.shared::cluster.global.mbarrier::complete_tx::bytes [%0], [%1], %2, [%3];"
               ::"r"(dst), "l"(src), "r"(bytes), "r"(bar) : "memory");
}
__device__ __forceinline__ void tma3d(uint32_t dst, const CUtensorMap* tm, int c0, int c1, int c2, uint32_t bar) {
  asm volatile("cp.async.bulk.tensor.3d.shared::cluster.global.mbarrier::complete_tx::bytes [%0], [%1, {%3, %4, %5}], [%2];"
               ::"r"(dst), "l"(tm), "r"(bar), "r"(c0), "r"(c1), "r"(c2) : "memory");
}
__device__ __forceinline__ uint32_t mapa(uint32_t addr, uint32_t rank) {
  uint32_t r;
  asm("mapa.shared::cluster.u32 %0, %1, %2;" : "=r"(r) : "r"(addr), "r"(rank));
  return r;
}
__device__ __forceinline__ float4 lds128f(uint32_t addr) {
  float4 v;
  asm volatile("ld.shared.v4.f32 {%0,%1,%2,%3}, [%4];" : "=f"(v.x), "=f"(v.y), "=f"(v.z), "=f"(v.w) : "r"(addr));
  return v;
}
__device__ __forceinline__ uint32_t lds32(uint32_t addr) {
  uint32_t v;
  asm volatile("ld.shared.u32 %0, [%1];" : "=r"(v) : "r"(addr));
  return v;
}
__device__ __forceinline__ void sts128(uint32_t addr, uint32_t a, uint32_t b, uint32_t c, uint32_t d) {
  asm volatile("st.shared.v4.u32 [%0], {%1,%2,%3,%4};" ::"r"(addr), "r"(a), "r"(b), "r"(c), "r"(d) : "memory");
}
#define WG_FENCE() asm volatile("wgmma.fence.sync.aligned;" ::: "memory")
#define WG_COMMIT() asm volatile("wgmma.commit_group.sync.aligned;" ::: "memory")
template <int n> __device__ __forceinline__ void wg_wait() {
  asm volatile("wgmma.wait_group.sync.aligned %0;" ::"n"(n) : "memory");
}
__device__ __forceinline__ uint32_t pack_bf16(float lo, float hi) {
  uint32_t r;
  asm("cvt.rn.bf16x2.f32 %0, %1, %2;" : "=r"(r) : "f"(hi), "f"(lo));
  return r;
}
__device__ __forceinline__ float bf_lo(uint32_t p) { return __uint_as_float(p << 16); }
__device__ __forceinline__ float bf_hi(uint32_t p) { return __uint_as_float(p & 0xffff0000u); }
__device__ __forceinline__ float bf_round(float x) { return __bfloat162float(__float2bfloat16_rn(x)); }
__device__ __forceinline__ uint32_t bf2_add(uint32_t a, uint32_t b) {
  uint32_t r;
  asm("add.rn.bf16x2 %0, %1, %2;" : "=r"(r) : "r"(a), "r"(b));
  return r;
}
__device__ __forceinline__ uint32_t bf2_mul(uint32_t a, uint32_t b) {
  uint32_t r;
  asm("mul.rn.bf16x2 %0, %1, %2;" : "=r"(r) : "r"(a), "r"(b));
  return r;
}
__device__ __forceinline__ float tanh_fast(float x) {
  float r;
  asm("tanh.approx.f32 %0, %1;" : "=f"(r) : "f"(x));
  return r;
}
__device__ __forceinline__ uint32_t bf2_fma(uint32_t a, uint32_t b, uint32_t c) {
  uint32_t r;
  asm("fma.rn.bf16x2 %0, %1, %2, %3;" : "=r"(r) : "r"(a), "r"(b), "r"(c));
  return r;
}
__device__ __forceinline__ float gelu_half(float hv) {
  const float p = fmaf(hv * hv, 8.0f * 0.0356774081363f, 2.0f * 0.7978845608029f);
  return fmaf(hv, tanh_fast(hv * p), hv);
}
__device__ __forceinline__ uint32_t gelu_pack(float a0, float a1, uint32_t hbias2) {
  const uint32_t hp = bf2_fma(pack_bf16(a0, a1), 0x3f003f00u, hbias2);
  return pack_bf16(gelu_half(bf_lo(hp)), gelu_half(bf_hi(hp)));
}

#define R8(a, o) "+f"(a[o]), "+f"(a[o + 1]), "+f"(a[o + 2]), "+f"(a[o + 3]), "+f"(a[o + 4]), "+f"(a[o + 5]), "+f"(a[o + 6]), "+f"(a[o + 7])
#define W8(a, o) "=f"(a[o]), "=f"(a[o + 1]), "=f"(a[o + 2]), "=f"(a[o + 3]), "=f"(a[o + 4]), "=f"(a[o + 5]), "=f"(a[o + 6]), "=f"(a[o + 7])
#define REGS48 "{%0,%1,%2,%3,%4,%5,%6,%7,%8,%9,%10,%11,%12,%13,%14,%15,%16,%17,%18,%19,%20,%21,%22,%23," \
               "%24,%25,%26,%27,%28,%29,%30,%31,%32,%33,%34,%35,%36,%37,%38,%39,%40,%41,%42,%43,%44,%45,%46,%47}"
#define REGS32 "{%0,%1,%2,%3,%4,%5,%6,%7,%8,%9,%10,%11,%12,%13,%14,%15,%16,%17,%18,%19,%20,%21,%22,%23," \
               "%24,%25,%26,%27,%28,%29,%30,%31}"
#define DESC_HI_A  "0x40000040"
#define DESC_HI_B1 "0x80000020"
#define DESC_HI_B2 "0x40000040"
template <bool ACC, int OA, int OB>
__device__ __forceinline__ void wgmma_ss_n96(float (&d)[48], uint32_t da, uint32_t db) {
  if (ACC)
    asm volatile("{\n.reg .b64 xa, xb;\n.reg .b32 la, lb;\nadd.u32 la, %48, %50;\nadd.u32 lb, %49, %51;\n"
                 "mov.b64 xa, {la, " DESC_HI_A "};\nmov.b64 xb, {lb, " DESC_HI_B1 "};\n"
                 "wgmma.mma_async.sync.aligned.m64n96k16.f32.bf16.bf16 " REGS48 ", xa, xb, 1, 1, 1, 0, 1;\n}\n"
                 : R8(d, 0), R8(d, 8), R8(d, 16), R8(d, 24), R8(d, 32), R8(d, 40) : "r"(da), "r"(db), "n"(OA), "n"(OB));
  else
    asm volatile("{\n.reg .b64 xa, xb;\n.reg .b32 la, lb;\nadd.u32 la, %48, %50;\nadd.u32 lb, %49, %51;\n"
                 "mov.b64 xa, {la, " DESC_HI_A "};\nmov.b64 xb, {lb, " DESC_HI_B1 "};\n"
                 "wgmma.mma_async.sync.aligned.m64n96k16.f32.bf16.bf16 " REGS48 ", xa, xb, 0, 1, 1, 0, 1;\n}\n"
                 : W8(d, 0), W8(d, 8), W8(d, 16), W8(d, 24), W8(d, 32), W8(d, 40) : "r"(da), "r"(db), "n"(OA), "n"(OB));
}
template <bool ACC, int OB>
__device__ __forceinline__ void wgmma_rs_n64(float (&d)[32], uint32_t a0, uint32_t a1, uint32_t a2, uint32_t a3, uint32_t db) {
  if (ACC)
    asm volatile("{\n.reg .b64 xb;\n.reg .b32 lb;\nadd.u32 lb, %36, %37;\nmov.b64 xb, {lb, " DESC_HI_B2 "};\n"
                 "wgmma.mma_async.sync.aligned.m64n64k16.f32.bf16.bf16 " REGS32 ", {%32,%33,%34,%35}, xb, 1, 1, 1, 1;\n}\n"
                 : R8(d, 0), R8(d, 8), R8(d, 16), R8(d, 24) : "r"(a0), "r"(a1), "r"(a2), "r"(a3), "r"(db), "n"(OB));
  else
    asm volatile("{\n.reg .b64 xb;\n.reg .b32 lb;\nadd.u32 lb, %36, %37;\nmov.b64 xb, {lb, " DESC_HI_B2 "};\n"
                 "wgmma.mma_async.sync.aligned.m64n64k16.f32.bf16.bf16 " REGS32 ", {%32,%33,%34,%35}, xb, 0, 1, 1, 1;\n}\n"
                 : W8(d, 0), W8(d, 8), W8(d, 16), W8(d, 24) : "r"(a0), "r"(a1), "r"(a2), "r"(a3), "r"(db), "n"(OB));
}
template <int N> __device__ __forceinline__ void fence_regs(float (&d)[N]) {
#pragma unroll
  for (int i = 0; i < N; i++) asm volatile("" : "+f"(d[i])::"memory");
}

constexpr int XS_BYTES = 9 * 16384;
constexpr int STAGE_BYTES = 12288;
constexpr int OFF_ST = XS_BYTES;
constexpr int OFF_B1 = OFF_ST + 6 * STAGE_BYTES;
constexpr int OFF_B2 = OFF_B1 + 1152;
constexpr int OFF_BAR = OFF_B2 + 1152;
constexpr int B_FULL = 0, B_X = 48  , B_RB = 120  , B_OWN = 152, B_FIN = 160, B_A8 = 168,
              B_EMPTY = 176  , B_TS = 224  , B_TS8 = 256, B_TR = 264  , B_P1L = 288, B_P1R = 296, B_U = 304,
              NBARS = 39;
constexpr int OFF_A8 = OFF_BAR + 512;
constexpr int OFF_ARGS = OFF_A8 + 2048;
constexpr int SMEM_BYTES = OFF_ARGS + 256 + 1024;
constexpr int OFF_STG = 65536, OFF_C8 = 131072;
constexpr int E_UA = 0, E_UB = 3616, E_W3A = 7232, E_W3B = 10848, E_W5 = 14464, E_W9 = 17568, E_TAP = 19680, E_SIZE = 23392;
constexpr int L_W7 = 4752, L_KB = 6832, L_Y = 6848, L_YB = 8304, L_SIZE = 28656;
constexpr int L_CONST = L_Y, L_KC = L_Y + 10240;
constexpr int TP_0 = 0, TP_W3A = 580, TP_UA = 716, TP_UB = 852, TP_W3B = 988, TP_W5 = 1248, TP_W9 = 1448, TP_W7 = 1648,
              TP_COPY = 1856;
__device__ __forceinline__ int e_off(int ch) { return ch == 0 ? 0 : OFF_ST + (ch - 1) * E_SIZE; }
__device__ __forceinline__ int l_off(int ch) { return 32768 + ch * L_SIZE; }
__device__ __forceinline__ int xg_off(int box) { return box < 4 ? OFF_ST + box * 4096 : 170880 + (box - 4) * 4096; }

__device__ __forceinline__ void ln_load(const __nv_bfloat16* __restrict__ x, const __nv_bfloat16* __restrict__ gate_w,
                                        int row, int lane, uint32_t (&w)[9], uint32_t (&gw)[9]) {
  const uint32_t* xr = reinterpret_cast<const uint32_t*>(x + (size_t)row * D_MOD) + lane;
  const uint32_t* gwp = reinterpret_cast<const uint32_t*>(gate_w) + lane;
#pragma unroll
  for (int j = 0; j < 9; j++) {
    asm volatile("ld.global.nc.u32 %0, [%1];" : "=r"(w[j]) : "l"(xr + j * 32));
    asm volatile("ld.global.nc.u32 %0, [%1];" : "=r"(gw[j]) : "l"(gwp + j * 32));
  }
}
__device__ __forceinline__ void ln_row(int row, int lane, const Scratch& sc, const uint32_t (&w)[9], const uint32_t (&gw)[9]) {
  float s = 0.f, gsum = 0.f;
#pragma unroll
  for (int j = 0; j < 9; j++) {
    uint32_t pr2 = bf2_mul(w[j], gw[j]);
    s += bf_lo(w[j]) + bf_hi(w[j]);
    gsum += bf_lo(pr2) + bf_hi(pr2);
  }
#pragma unroll
  for (int o = 1; o < 32; o <<= 1) { s += __shfl_xor_sync(~0u, s, o); gsum += __shfl_xor_sync(~0u, gsum, o); }
  const float mean = s * (1.0f / 576.0f);
  float vs = 0.f;
#pragma unroll
  for (int j = 0; j < 9; j++) {
    float d0 = bf_lo(w[j]) - mean, d1 = bf_hi(w[j]) - mean;
    vs = fmaf(d0, d0, vs); vs = fmaf(d1, d1, vs);
  }
#pragma unroll
  for (int o = 1; o < 32; o <<= 1) vs += __shfl_xor_sync(~0u, vs, o);
  const float mb = bf_round(mean);
  const float vb = bf_round(vs * (1.0f / 576.0f));
  const float rinv = __frcp_rn(bf_round(__fsqrt_rn(bf_round(vb + 1e-5f))));
  const uint32_t nm2 = pack_bf16(-mb, -mb);
  uint32_t* dst = reinterpret_cast<uint32_t*>(sc.xn + (size_t)row * D_MOD) + lane;
#pragma unroll
  for (int j = 0; j < 9; j++) {
    uint32_t dd = bf2_add(w[j], nm2);
    dst[j * 32] = pack_bf16(bf_lo(dd) * rinv, bf_hi(dd) * rinv);
  }
  if (lane == 0) {
    float gv = bf_round(__fdividef(1.0f, 1.0f + __expf(-bf_round(gsum))));
    float og = bf_round(1.0f - gv);
    sc.gate[row] = make_uint2(pack_bf16(gv, gv), pack_bf16(og, og));
  }
}
__device__ __forceinline__ void mma_bf16(float (&d)[4], uint32_t a0, uint32_t a1, uint32_t a2, uint32_t a3, uint32_t b0, uint32_t b1) {
  asm("mma.sync.aligned.m16n8k16.row.col.f32.bf16.bf16.f32 {%0,%1,%2,%3}, {%4,%5,%6,%7}, {%8,%9}, {%0,%1,%2,%3};"
      : "+f"(d[0]), "+f"(d[1]), "+f"(d[2]), "+f"(d[3]) : "r"(a0), "r"(a1), "r"(a2), "r"(a3), "r"(b0), "r"(b1));
}
__device__ __forceinline__ void mma_tf32(float (&d)[4], float a0, float a1, float a2, float a3, float b0, float b1) {
  asm("mma.sync.aligned.m16n8k8.row.col.f32.tf32.tf32.f32 {%0,%1,%2,%3}, {%4,%5,%6,%7}, {%8,%9}, {%0,%1,%2,%3};"
      : "+f"(d[0]), "+f"(d[1]), "+f"(d[2]), "+f"(d[3])
      : "r"(__float_as_uint(a0)), "r"(__float_as_uint(a1)), "r"(__float_as_uint(a2)), "r"(__float_as_uint(a3)),
        "r"(__float_as_uint(b0)), "r"(__float_as_uint(b1)));
}
__device__ __forceinline__ float2 cexp_l(float al, float th, float l) {
  float mg;
  asm("ex2.approx.ftz.f32 %0, %1;" : "=f"(mg) : "f"(al * l));
  const float tr = th * l;
  return make_float2(mg * __cosf(tr), mg * __sinf(tr));
}
__device__ __forceinline__ float2 cmul(float2 a, float2 b) {
  return make_float2(fmaf(a.x, b.x, -a.y * b.y), fmaf(a.x, b.y, a.y * b.x));
}
__device__ __forceinline__ float2 cmulc(float2 a, float2 b) {
  return make_float2(fmaf(a.x, b.x, -a.y * b.y), fmaf(-a.x, b.y, -a.y * b.x));
}
__device__ __forceinline__ float2 csq(float2 a) { return make_float2(fmaf(a.x, a.x, -a.y * a.y), 2.0f * a.x * a.y); }
#define SM_U32(p) (*reinterpret_cast<uint32_t*>(p))
#define SM_F32(p) (*reinterpret_cast<float*>(p))
#define SM_U16(p) (*reinterpret_cast<unsigned short*>(p))
#define SM_U2(p) (*reinterpret_cast<uint2*>(p))
#define SM_F2(p) (*reinterpret_cast<float2*>(p))
#define SM_U4(p) (*reinterpret_cast<uint4*>(p))
#define SM_F4(p) (*reinterpret_cast<float4*>(p))
template <int OFF, int TAG>
__device__ __forceinline__ uint32_t lds_free(uint32_t base) {
  uint32_t v;
  asm volatile("ld.volatile.shared.u32 %0, [%1+%2]; // %3" : "=r"(v) : "r"(base), "n"(OFF), "n"(TAG));
  return v;
}
template <int K0, int K1, int OFF, int K>
__device__ __forceinline__ void load_tquads_(uint32_t (&q)[K1 - K0][4], uint32_t tp) {
  if constexpr (K >= K0) {
    q[K - K0][0] = lds_free<OFF - 32 * K, 0>(tp);
    q[K - K0][1] = lds_free<OFF - 32 * K - 16, 1>(tp);
    q[K - K0][2] = lds_free<OFF - 32 * K + 16, 2>(tp);
    q[K - K0][3] = lds_free<OFF - 32 * K, 3>(tp);
    load_tquads_<K0, K1, OFF, K - 1>(q, tp);
  }
}
template <int K0, int K1, int OFF>
__device__ __forceinline__ void load_tquads(uint32_t (&q)[K1 - K0][4], uint32_t tp) {
  load_tquads_<K0, K1, OFF, K1 - 1>(q, tp);
}
__device__ __forceinline__ void ldsm4_free(uint32_t (&r)[4], uint32_t addr) {
  asm("ldmatrix.sync.aligned.m8n8.x4.shared.b16 {%0,%1,%2,%3}, [%4];"
      : "=r"(r[0]), "=r"(r[1]), "=r"(r[2]), "=r"(r[3]) : "r"(addr));
}
__device__ __forceinline__ void ldsm4t_free(uint32_t (&r)[4], uint32_t addr) {
  asm("ldmatrix.sync.aligned.m8n8.x4.trans.shared.b16 {%0,%1,%2,%3}, [%4];"
      : "=r"(r[0]), "=r"(r[1]), "=r"(r[2]), "=r"(r[3]) : "r"(addr));
}
__device__ __forceinline__ uint32_t ldg_u16(const __nv_bfloat16* p) {
  unsigned short v;
  asm volatile("ld.global.nc.u16 %0, [%1];" : "=h"(v) : "l"(p));
  return v;
}
__device__ __forceinline__ void ldsm4t(uint32_t (&r)[4], uint32_t addr) {
  asm volatile("ldmatrix.sync.aligned.m8n8.x4.trans.shared.b16 {%0,%1,%2,%3}, [%4];"
               : "=r"(r[0]), "=r"(r[1]), "=r"(r[2]), "=r"(r[3]) : "r"(addr) : "memory");
}
template <int I0, int I1, int K0, int K1, int JMIN, int RB, int TOFF>
__device__ __forceinline__ void band(float (&acc)[I1 - I0][4], uint32_t tp, uint32_t sa, uint32_t za, int lane) {
  uint32_t tq[K1 - K0][4];
  load_tquads<K0, K1, TOFF>(tq, tp);
  constexpr int JL = (I0 - K1 + 1 > JMIN) ? I0 - K1 + 1 : JMIN, JH = I1 - 1 - K0;
  constexpr int JP = (JL >= 0) ? (JL & ~1) : -2;
#pragma unroll
  for (int J2 = JP; J2 <= JH; J2 += 2) {
    uint32_t b[4];
    ldsm4t_free(b, (J2 < 0 && lane < 31) ? za : sa + J2 * 16 * RB);
#pragma unroll
    for (int hf = 0; hf < 2; hf++) {
      const int J = J2 + hf;
#pragma unroll
      for (int k = K0; k < K1; k++) {
        const int I = J + k;
        if (J >= JL && J <= JH && I >= I0 && I < I1)
          mma_bf16(acc[I - I0], tq[k - K0][0], tq[k - K0][1], tq[k - K0][2], tq[k - K0][3], b[2 * hf], b[2 * hf + 1]);
      }
    }
  }
}
template <int I0, int I1>
__device__ __forceinline__ void p8_tiles(uint32_t ea, uint32_t za, char* lb, uint32_t tp, int lane) {
  float acc[I1 - I0][4];
#pragma unroll
  for (int i = 0; i < I1 - I0; i++) { acc[i][0] = acc[i][1] = acc[i][2] = acc[i][3] = 0.f; }
  const uint32_t sa = ea + 32 + lane * 16;
  band<I0, I1, 2, 5, -1, 16, TP_W3A + 160>(acc, tp, sa + E_W3A, za, lane);
  band<I0, I1, 2, 5, 0, 16, TP_UA + 160>(acc, tp, sa + E_UA, za, lane);
  band<I0, I1, 2, 5, 0, 16, TP_UB + 160>(acc, tp, sa + E_UB, za, lane);
  band<I0, I1, 2, 9, 0, 16, TP_W3B + 288>(acc, tp, sa + E_W3B, za, lane);
  band<I0, I1, 4, 9, -1, 16, TP_W5 + 288>(acc, tp, sa + E_W5, za, lane);
  char* a = lb + L_Y + L_YB + 4 * (8 * (lane >> 2) + 2 * (lane & 3));
#pragma unroll
  for (int I = I0; I < I1; I++) {
    SM_F2(a + 4 * (128 * I + 4 * (I >> 1))) = make_float2(acc[I - I0][0], acc[I - I0][1]);
    SM_F2(a + 4 * (128 * I + 4 * (I >> 1)) + 256) = make_float2(acc[I - I0][2], acc[I - I0][3]);
  }
}

struct MlpCtx {
  uint32_t bars;
  uint32_t dA, dB;
  int lane;
};
__device__ __forceinline__ void stage_release(const MlpCtx& c, int slot) {
  if (c.lane == 0) mbar_arrive(c.bars + B_EMPTY + 8 * slot);
}
template <int P>
__device__ __forceinline__ void gelu_part(uint32_t baddr, float (&acc)[48]) {
  asm volatile("" : R8(acc, P * 8)::"memory");
  const uint32_t b0 = bf2_mul(lds32(baddr + P * 32), 0x3f003f00u), b1 = bf2_mul(lds32(baddr + P * 32 + 16), 0x3f003f00u);
  uint32_t r0 = gelu_pack(acc[P * 8 + 0], acc[P * 8 + 1], b0);
  uint32_t r1 = gelu_pack(acc[P * 8 + 2], acc[P * 8 + 3], b0);
  uint32_t r2 = gelu_pack(acc[P * 8 + 4], acc[P * 8 + 5], b1);
  uint32_t r3 = gelu_pack(acc[P * 8 + 6], acc[P * 8 + 7], b1);
  acc[P * 8 + 0] = __uint_as_float(r0);
  acc[P * 8 + 1] = __uint_as_float(r1);
  acc[P * 8 + 2] = __uint_as_float(r2);
  acc[P * 8 + 3] = __uint_as_float(r3);
}
__device__ __forceinline__ void h_push(uint32_t (&h)[144], float (&acc)[48]) {
  asm volatile("" : R8(acc, 0)::"memory");
#pragma unroll
  for (int i = 0; i < 96; i++) h[i] = h[i + 24];
#pragma unroll
  for (int i = 0; i < 24; i++) h[96 + i] = __float_as_uint(acc[(i >> 2) * 8 + (i & 3)]);
}
template <int SB, int I>
__device__ __forceinline__ void p1_mma(const MlpCtx& c, float (&cur)[48]) {
  constexpr int S = SB % 9;
  wgmma_ss_n96<(S | I) != 0, ((S * 16384 + I * 32) >> 4),
               (4096 >> 4 << 16) + (((SB % 6) * STAGE_BYTES + I * 1024) >> 4)>(cur, c.dA, c.dB);
}
template <int SB>
__device__ __forceinline__ void p1_stage(const MlpCtx& c, int j, uint32_t baddr, float (&cur)[48], float (&prev)[48],
                                         uint32_t (&h)[144]) {
  constexpr int S = SB % 9;
  if (SB < 9) mbar_wait(c.bars + B_X + 8 * S, 0);
  mbar_wait(c.bars + B_FULL + 8 * (SB % 6), ((SB / 6) + j) & 1);
  WG_FENCE();
  p1_mma<SB, 0>(c, cur); p1_mma<SB, 1>(c, cur); p1_mma<SB, 2>(c, cur); p1_mma<SB, 3>(c, cur);
  WG_COMMIT();
  if (S >= 1 && S <= 6) gelu_part<(S >= 1 && S <= 6) ? S - 1 : 0>(baddr, prev);
  if (S == 7) h_push(h, prev);
  wg_wait<1>();
  if (SB > 0 || j > 0) stage_release(c, (SB + 5) % 6);
  if (S == 0) fence_regs(prev);
}
template <int SB0>
__device__ __forceinline__ void p1_chunk(const MlpCtx& c, int j, uint32_t baddr, float (&cur)[48], float (&prev)[48],
                                         uint32_t (&h)[144]) {
  p1_stage<SB0 + 0>(c, j, baddr, cur, prev, h); p1_stage<SB0 + 1>(c, j, baddr, cur, prev, h);
  p1_stage<SB0 + 2>(c, j, baddr, cur, prev, h); p1_stage<SB0 + 3>(c, j, baddr, cur, prev, h);
  p1_stage<SB0 + 4>(c, j, baddr, cur, prev, h); p1_stage<SB0 + 5>(c, j, baddr, cur, prev, h);
  p1_stage<SB0 + 6>(c, j, baddr, cur, prev, h); p1_stage<SB0 + 7>(c, j, baddr, cur, prev, h);
  p1_stage<SB0 + 8>(c, j, baddr, cur, prev, h);
}
template <int S, int I>
__device__ __forceinline__ void p2_one(const MlpCtx& c, float (&cur)[32], uint32_t (&h)[144]) {
  constexpr int kk = 6 * S + I;
  wgmma_rs_n64<(S | I) != 0, ((S * STAGE_BYTES + I * 2048) >> 4)>(cur, h[4 * kk], h[4 * kk + 1], h[4 * kk + 2], h[4 * kk + 3], c.dB);
}
template <int S>
__device__ __forceinline__ void p2_mma(const MlpCtx& c, uint32_t parity, float (&cur)[32], uint32_t (&h)[144]) {
  mbar_wait(c.bars + B_FULL + 8 * S, parity);
  WG_FENCE();
  p2_one<S, 0>(c, cur, h); p2_one<S, 1>(c, cur, h); p2_one<S, 2>(c, cur, h);
  p2_one<S, 3>(c, cur, h); p2_one<S, 4>(c, cur, h); p2_one<S, 5>(c, cur, h);
  WG_COMMIT();
}
__device__ __forceinline__ int chunk_of(int pos, int pr, int rank) {
  const int off = (int)(0x03231201ull >> (4 * pos)) & 3;
  const int mine = (0x168 >> pos) & 1;
  return pos == 1 ? 8 : 2 * ((pr + off) & 3) + (mine ? rank : rank ^ 1);
}
__device__ __forceinline__ void bulk_s2peer(uint32_t rdst, uint32_t src, uint32_t bytes, uint32_t rbar) {
  asm volatile("cp.async.bulk.shared::cluster.shared::cta.mbarrier::complete_tx::bytes [%0], [%1], %2, [%3];"
               ::"r"(rdst), "r"(src), "r"(bytes), "r"(rbar) : "memory");
}
__device__ __forceinline__ void bulk_s2g_release(void* gdst, uint32_t src, uint32_t bytes) {
  asm volatile("cp.async.bulk.global.shared::cta.bulk_group [%0], [%1], %2;\n"
               "cp.async.bulk.commit_group;\ncp.async.bulk.wait_group 0;\nfence.acq_rel.gpu;"
               ::"l"(gdst), "r"(src), "r"(bytes) : "memory");
}
struct Args {
  const __nv_bfloat16 *u, *Are, *Aim, *Bre, *Bim, *Cre, *Cim, *logdt, *Dskip, *gate_w, *w1, *w2, *b1, *b2;
  __nv_bfloat16* out;
};

struct Maps { const CUtensorMap *x, *w1, *xn; };
__device__ __forceinline__ void load_params(uint32_t (&v)[8], const Args& ar, int d, int n) {
  const int idx = d * N_ST + n;
  v[0] = ldg_u16(ar.Are + idx); v[1] = ldg_u16(ar.Aim + idx); v[2] = ldg_u16(ar.Bre + idx); v[3] = ldg_u16(ar.Bim + idx);
  v[4] = ldg_u16(ar.Cre + idx); v[5] = ldg_u16(ar.Cim + idx); v[6] = ldg_u16(ar.logdt + d); v[7] = ldg_u16(ar.Dskip + d);
}
__device__ __forceinline__ uint4 pack_params(uint32_t (&v)[8]) {
  asm volatile("" : "+r"(v[0]), "+r"(v[1]), "+r"(v[2]), "+r"(v[3]), "+r"(v[4]), "+r"(v[5]), "+r"(v[6]), "+r"(v[7])::"memory");
  return make_uint4(v[0] | (v[1] << 16), v[2] | (v[3] << 16), v[4] | (v[5] << 16), v[6] | (v[7] << 16));
}
__device__ __noinline__ uint4 ssm_pass(const Maps tm, char* sm, const int d0, const int pass, const uint4 pv
) {
  const Args& ar = *reinterpret_cast<const Args*>(sm + OFF_ARGS);
  const Scratch& sc = *reinterpret_cast<const Scratch*>(sm + OFF_ARGS + 128);
  const uint32_t sb = smem_u32(sm), bars = sb + OFF_BAR;
  const int tid = threadIdx.x, lane = tid & 31;
  const int warp = __shfl_sync(0xffffffffu, tid >> 5, 0);
  const int bid = blockIdx.x, m = bid >> 3, f = bid & 7;
  const int g = lane >> 2, cc = lane & 3;
  const int ch = warp >> 2, n = tid & 127;
  char* eb = sm + e_off(ch);
  char* lb = sm + l_off(ch);
#define CH_SYNC() asm volatile("bar.sync %0, 128;" ::"r"(ch + 1) : "memory")
  {
    const float are = bf_lo(pv.x), aim = bf_hi(pv.x), bre = bf_lo(pv.y), bim = bf_hi(pv.y);
    const float cre = bf_lo(pv.z), cim = bf_hi(pv.z), ldt = bf_lo(pv.w), dsk = bf_hi(pv.w);
    const float dt = bf_round(expf(ldt));
    const float al = (dt * are) * 1.4426950408889634f, th = dt * aim;
    constexpr float TF32_UNBIAS = 1.0f + 0.7f / 1024.0f;
    const float2 c0 = cmul(make_float2(cre * TF32_UNBIAS, cim * TF32_UNBIAS), make_float2(dt * bre, dt * bim));
    const float2 e64 = cexp_l(al, th, 64.f), e128 = csq(e64), e256 = cexp_l(al, th, 256.f), e512 = csq(e256);
    const float2 k128 = cmul(c0, e128), k256 = cmul(c0, e256), k384 = cmul(k256, e128);
    const float2 k512 = cmul(c0, e512), k516 = cmul(k512, cexp_l(al, th, 4.f));
    const float2 e1024 = cexp_l(al, th, 1024.f), k1024 = cmul(c0, e1024);
    float k2048 = fmaf(k1024.x, e1024.x, -k1024.y * e1024.y) * (1.0f / TF32_UNBIAS);
    char* ca = lb + L_CONST + n * 80;
    SM_F4(ca) = make_float4(al, th, e64.x, e64.y);
    SM_F4(ca + 16) = make_float4(c0.x, c0.y, k128.x, k128.y);
    SM_F4(ca + 32) = make_float4(k256.x, k256.y, k384.x, k384.y);
    SM_F4(ca + 48) = make_float4(k512.x, k512.y, k516.x, k516.y);
    SM_F2(ca + 64) = k1024;
#pragma unroll
    for (int o = 16; o > 0; o >>= 1) k2048 += __shfl_xor_sync(~0u, k2048, o);
    if (lane == 0) SM_F32(lb + L_KC + (warp & 3) * 2576 + 2560) = k2048;
    if (n == 0) SM_F32(lb + L_KB + 8) = dsk;
    __syncwarp();
    DBG_S(0);
    float kd[5][4];
#pragma unroll
    for (int t = 0; t < 5; t++) { kd[t][0] = kd[t][1] = kd[t][2] = kd[t][3] = 0.f; }
    const float l1 = (float)g, l128 = (float)(128 * g);
    const char* cr = lb + L_CONST + ((warp & 3) * 32 + cc) * 80;
    const int o2 = 32 + (g >> 2) * 8, o3 = 48 + (g & 1) * 8, s2 = ((g & 3) << 2) | cc, s3 = ((g >> 1) << 2) | cc;
#pragma unroll 2
    for (int st = 0; st < 8; st++, cr += 320) {
      const float4 q0 = *(const float4*)cr, q1 = *(const float4*)(cr + 16);
      const float2 q2 = *(const float2*)(cr + o2), q3 = *(const float2*)(cr + o3), q4 = *(const float2*)(cr + 64);
      const float2 p1 = cexp_l(q0.x, q0.y, l1), p128 = cexp_l(q0.x, q0.y, l128);
      const float2 p2 = csq(p1), p8 = csq(csq(p2));
      const float2 a1 = cmul(p8, make_float2(q0.z, q0.w));
      float2 x = cmulc(make_float2(q1.x, q1.y), p1);
      mma_tf32(kd[0], p8.x, a1.x, p8.y, a1.y, x.x, x.y);
      x = cmulc(make_float2(q1.z, q1.w), p1);
      mma_tf32(kd[1], p8.x, a1.x, p8.y, a1.y, x.x, x.y);
      x = cmulc(q2, make_float2(__shfl_sync(~0u, p2.x, s2), __shfl_sync(~0u, p2.y, s2)));
      mma_tf32(kd[2], p8.x, a1.x, p8.y, a1.y, x.x, x.y);
      x = cmulc(q3, make_float2(__shfl_sync(~0u, p128.x, s3), __shfl_sync(~0u, p128.y, s3)));
      mma_tf32(kd[3], p8.x, a1.x, p8.y, a1.y, x.x, x.y);
      x = cmulc(q4, p128);
      mma_tf32(kd[4], p8.x, a1.x, p8.y, a1.y, x.x, x.y);
    }
    char* kc = lb + L_KC + (warp & 3) * 2576;
#pragma unroll
    for (int e = 0; e < 2; e++) {
      const int row = g + e * 8;
      SM_F2(kc + 4 * (8 * row + 2 * cc)) = make_float2(kd[0][2 * e], kd[0][2 * e + 1]);
      SM_F2(kc + 4 * (128 + 8 * row + 2 * cc)) = make_float2(kd[1][2 * e], kd[1][2 * e + 1]);
      SM_F2(kc + 4 * (256 + 64 * (cc >> 1) + 4 * row + 2 * (cc & 1))) = make_float2(kd[2][2 * e], kd[2][2 * e + 1]);
      SM_F2(kc + 4 * (384 + 32 * cc + 2 * row)) = make_float2(kd[3][2 * e], kd[3][2 * e + 1]);
      SM_F32(kc + 4 * (512 + 32 * cc + row)) = kd[4][2 * e];
      SM_F32(kc + 4 * (528 + 32 * cc + row)) = kd[4][2 * e + 1];
    }
  }
  DBG_S(1);
  uint32_t lw[9], lg[9];
  ln_load(ar.u, ar.gate_w, (bid & 127) * 16 + warp, lane, lw, lg);
  CH_SYNC();
  {
    const char* kc = lb + L_KC;
    auto kq = [&](int idx) {
      const char* q = kc + 4 * idx;
      return (*(const float*)q + *(const float*)(q + 2576)) + (*(const float*)(q + 5152) + *(const float*)(q + 7728));
    };
#pragma unroll
    for (int it = 0; it < 5; it++) {
      const int idx = n + 128 * it;
      float t = kq(idx);
      if ((it == 1 || it == 2) && n == 127) t -= kq(idx + 1);
      if (it == 4 && n == 0) { SM_F2(lb + L_KB) = make_float2(t, kq(640)); t = 0.f; }
      int off;
      if (it < 2) off = TP_0 + 2 * (272 - idx);
      else if (it == 2) {
        const int sel = n & 3, mu = 32 + (n >> 2);
        off = sel == 2 ? TP_W3B + 2 * (144 - mu) : (sel == 0 ? TP_W3A : sel == 1 ? TP_UA : TP_UB) + 2 * (80 - mu);
      } else if (it == 3) off = ((n & 1) ? TP_W3B : TP_W5) + 2 * (80 - (n >> 1));
      else off = ((n & 1) ? TP_W7 : TP_W9) + 2 * (80 - (n >> 1));
      const unsigned short hv = pack_bf16(t, 0.f);
      SM_U16(eb + E_TAP + off) = hv;
      SM_U16(eb + E_TAP + TP_COPY + off + 2) = hv;
    }
  }
  DBG_S(2);
  if (bid < 128) ln_row(bid * 16 + warp, lane, sc, lw, lg);
  DBG_S(3);
  mbar_wait(bars + B_U, pass & 1);
  {
    const uint32_t src = sb + xg_off(warp >> 1) + ((warp & 1) * 128 + lane) * 16;
    const int mych = g - (d0 & 4);
    char* dst = sm + l_off(mych) + ((warp >> 1) + 1) * 528 + (warp & 1) * 256 + cc * 4;
#pragma unroll
    for (int i = 0; i < 4; i++) {
      uint32_t r[4];
      ldsm4t(r, src + i * 512);
      if (mych >= 0 && mych < 4) {
#pragma unroll
        for (int k = 0; k < 4; k++) SM_U32(dst + i * 64 + k * 16) = r[k];
      }
    }
  }
  __syncthreads();
  DBG_S(4);
  if (bid < 128) {
    if (tid == 480) {
      asm volatile("fence.acq_rel.gpu;" ::: "memory");
      atomicAdd(&sc.flags[256 + m], 1u);
    } else if (tid == 0) {
      asm volatile("cp.async.bulk.prefetch.L2.global [%0], %1;" ::"l"(ar.w1 + (size_t)bid * 20736), "r"(41472) : "memory");
      asm volatile("cp.async.bulk.prefetch.L2.global [%0], %1;" ::"l"(ar.w2 + (size_t)bid * 20736), "r"(41472) : "memory");
    }
  }
#pragma unroll 1
  for (int i = n - 1; i < 224; i += 128) {
    const char* ur = lb + ((i >> 5) + 1) * 528 + (i & 31) * 16;
    const uint4 w0 = *(const uint4*)(ur - ((i & 31) ? 16 : 32) + (i < 0 ? 16 : 0)), w1 = *(const uint4*)ur,
                w2 = *(const uint4*)(ur + ((i & 31) == 31 ? 32 : 16));
    const uint32_t wv[12] = {w0.x, w0.y, w0.z, w0.w, w1.x, w1.y, w1.z, w1.w, w2.x, w2.y, w2.z, w2.w};
    char* o = eb + 32 + 16 * i;
    SM_U4(o + E_UA) = make_uint4(wv[3], wv[4], wv[5], wv[6]);
    SM_U4(o + E_UB) = make_uint4(wv[1], wv[2], wv[3], wv[4]);
    float v[22], wa[16];
#pragma unroll
    for (int k = 1; k < 11; k++) { v[2 * k] = bf_lo(wv[k]); v[2 * k + 1] = bf_hi(wv[k]); }
#pragma unroll
    for (int k = 4; k < 16; k++) wa[k] = (v[k - 1] + v[k]) + v[k + 1];
    SM_U4(o + E_W3A) = make_uint4(pack_bf16(wa[8], wa[9]), pack_bf16(wa[10], wa[11]), pack_bf16(wa[12], wa[13]), pack_bf16(wa[14], wa[15]));
    SM_U4(o + E_W3B) = make_uint4(pack_bf16(wa[4], wa[5]), pack_bf16(wa[6], wa[7]), pack_bf16(wa[8], wa[9]), pack_bf16(wa[10], wa[11]));
    if (i < 192) {
#pragma unroll
      for (int k = 8; k < 16; k++) wa[k] += v[k - 2] + v[k + 2];
      SM_U4(o + E_W5) = make_uint4(pack_bf16(wa[8], wa[9]), pack_bf16(wa[10], wa[11]), pack_bf16(wa[12], wa[13]), pack_bf16(wa[14], wa[15]));
      if (i < 128) {
#pragma unroll
        for (int k = 8; k < 16; k++) wa[k] += v[k - 3] + v[k + 3];
        SM_U4(lb + L_W7 + 32 + 16 * i) =
            make_uint4(pack_bf16(wa[8], wa[9]), pack_bf16(wa[10], wa[11]), pack_bf16(wa[12], wa[13]), pack_bf16(wa[14], wa[15]));
#pragma unroll
        for (int k = 8; k < 16; k++) wa[k] += v[k - 4] + v[k + 4];
        SM_U4(o + E_W9) = make_uint4(pack_bf16(wa[8], wa[9]), pack_bf16(wa[10], wa[11]), pack_bf16(wa[12], wa[13]), pack_bf16(wa[14], wa[15]));
      }
    }
  }
  CH_SYNC();
  DBG_S(5);
  {
    const int role = (warp + ch) & 3;
    uint32_t ea = smem_u32(eb), za = smem_u32(lb);
    asm volatile("" : "+r"(ea), "+r"(za)::"memory");
    const uint32_t tp = ea + E_TAP + ((g & 1) ? TP_COPY + 2 : 0) - 2 * (g - 2 * cc);
    if (role < 2) {
      uint32_t ta[17][4];
      load_tquads<0, 17, TP_0 + 544>(ta, tp);
      float acc[8][4];
#pragma unroll
      for (int i = 0; i < 8; i++) { acc[i][0] = acc[i][1] = acc[i][2] = acc[i][3] = 0.f; }
      const uint32_t bpos = za + ((lane & 7) + 1) * 528 + role * 256 + (lane >> 3) * 16;
      const uint32_t bmid = role ? bpos : bpos - 16;
#pragma unroll
      for (int j2 = -16; j2 < 8; j2 += 2) {
        uint32_t b[4];
        ldsm4_free(b, (j2 < -8 ? bpos - 16 : j2 < 0 ? bmid : bpos) + 32 * j2);
#pragma unroll
        for (int hf = 0; hf < 2; hf++) {
#pragma unroll
          for (int i = 0; i < 8; i++) {
            const int k = i - j2 - hf;
            if (k >= 0 && k <= 16) mma_bf16(acc[i], ta[k][0], ta[k][1], ta[k][2], ta[k][3], b[2 * hf], b[2 * hf + 1]);
          }
        }
      }
      char* ya = lb + L_Y + 4 * (520 * cc + 128 * role + g);
#pragma unroll
      for (int i = 0; i < 8; i++) {
        SM_F32(ya + 64 * i) = acc[i][0]; SM_F32(ya + 64 * i + 1040) = acc[i][1];
        SM_F32(ya + 64 * i + 32) = acc[i][2]; SM_F32(ya + 64 * i + 1072) = acc[i][3];
      }
    } else if (role == 2) {
      p8_tiles<1, 11>(ea, za, lb, tp, lane);
    } else {
      p8_tiles<11, 16>(ea, za, lb, tp, lane);
      float acc[2][5][4];
#pragma unroll
      for (int i = 0; i < 10; i++) { acc[i / 5][i % 5][0] = acc[i / 5][i % 5][1] = acc[i / 5][i % 5][2] = acc[i / 5][i % 5][3] = 0.f; }
#pragma unroll
      for (int sg = 0; sg < 2; sg++) {
        uint32_t tq[5][4];
        if (sg == 0) load_tquads<4, 9, TP_W9 + 288>(tq, tp); else load_tquads<4, 9, TP_W7 + 288>(tq, tp);
        const uint32_t sa = (sg == 0 ? ea + E_W9 : za + L_W7 - 16) + 32 + (lane & 15) * 32 + (lane >> 4) * 16;
#pragma unroll
        for (int J = -1 + sg; J < 4; J++) {
          uint32_t b[4];
          ldsm4t_free(b, (J < 0 && (lane & 15) < 15) ? za : sa + J * 512);
#pragma unroll
          for (int k = 4; k < 9; k++) {
            const int I = J + k;
            if (I < 8) {
              mma_bf16(acc[0][I - 3], tq[k - 4][0], tq[k - 4][1], tq[k - 4][2], tq[k - 4][3], b[0], b[1]);
              mma_bf16(acc[1][I - 3], tq[k - 4][0], tq[k - 4][1], tq[k - 4][2], tq[k - 4][3], b[2], b[3]);
            }
          }
        }
      }
      char* a = lb + L_Y + 2 * L_YB + 4 * (16 * g + 2 * cc);
#pragma unroll
      for (int hh = 0; hh < 2; hh++) {
#pragma unroll
        for (int I = 3; I < 8; I++) {
          SM_F2(a + 32 * hh + 1040 * (I - 3)) = make_float2(acc[hh][I - 3][0], acc[hh][I - 3][1]);
          SM_F2(a + 32 * hh + 1040 * (I - 3) + 512) = make_float2(acc[hh][I - 3][2], acc[hh][I - 3][3]);
        }
      }
    }
  }
  __syncthreads();
  DBG_S(6);
  if (lane == 0) {
    HFENCE();
    if (bid >= 128) {
      if (pass < 3 && (warp & 1) == 0) {
        mbar_expect_tx(bars + B_U, 4096);
        tma2d(sb + xg_off(warp >> 1), tm.x, (d0 + 4) & ~7, (warp >> 1) * 256, bars + B_U);
      }
    } else if (warp < 6) {
      mbar_expect_tx(bars + B_FULL + 8 * warp, STAGE_BYTES);
      tma3d(sb + OFF_ST + warp * STAGE_BYTES, tm.w1, 0, warp * 64, f * 18, bars + B_FULL + 8 * warp);
    } else if (warp < 8) {
      wait_flag(&sc.flags[256 + m], 8);
      mbar_expect_tx(bars + B_X + 8 * (warp - 6), 16384);
      tma2d(sb + (warp - 6) * 16384, tm.xn, (warp - 6) * 64, m * 128, bars + B_X + 8 * (warp - 6));
    }
  }
  __syncwarp();
  uint32_t pnext[8];
#pragma unroll
  for (int i = 0; i < 8; i++) pnext[i] = 0;
  if (bid >= 128 && pass < 3) load_params(pnext, ar, d0 + 4 + ch, n);
  {
    const float4 kb = SM_F4(lb + L_KB);
    const uint32_t dk = pack_bf16(kb.z, kb.z);
#pragma unroll
    for (int k = 0; k < 4; k++) {
      const int t0 = n * 4 + 512 * k;
      char* ya = lb + L_Y + 4 * (t0 + 4 * (t0 >> 8));
      float4 y = SM_F4(ya);
      if (k > 0 || t0 >= 128) { const float4 b = SM_F4(ya + L_YB); y.x += b.x; y.y += b.y; y.z += b.z; y.w += b.w; }
      if (k > 1 || (k == 1 && t0 >= 768)) {
        const float4 b = SM_F4(ya + 2 * L_YB - 3120);
        y.x += b.x; y.y += b.y; y.z += b.z; y.w += b.w;
        if (k > 1 || t0 >= 1020) {
          const char* wp = lb + L_W7 + 32 + 2 * (t0 - 1026);
          const uint32_t wl = *(const uint32_t*)wp, wm = *(const uint32_t*)(wp + 4), wh = *(const uint32_t*)(wp + 8);
          y.x = fmaf(kb.x, bf_hi(wl), y.x); y.y = fmaf(kb.x, bf_lo(wm), y.y);
          y.z = fmaf(kb.x, bf_hi(wm), y.z); y.w = fmaf(kb.x, bf_lo(wh), y.w);
          if (k == 3 && n == 127) {
            const uint2 u03 = SM_U2(lb + 528);
            float pre = bf_lo(u03.x);
            y.x = fmaf(kb.y, pre, y.x); pre += bf_hi(u03.x);
            y.y = fmaf(kb.y, pre, y.y); pre += bf_lo(u03.y);
            y.z = fmaf(kb.y, pre, y.z); pre += bf_hi(u03.y);
            y.w = fmaf(kb.y, pre, y.w);
          }
        }
      }
      const uint2 uu = SM_U2(lb + ((t0 >> 8) + 1) * 528 + (t0 & 255) * 2);
      uint2 o;
      o.x = bf2_add(pack_bf16(y.x, y.y), bf2_mul(uu.x, dk));
      o.y = bf2_add(pack_bf16(y.z, y.w), bf2_mul(uu.y, dk));
      *reinterpret_cast<uint2*>(sc.aT + (size_t)(d0 + ch) * L_SEQ + t0) = o;
    }
  }
  __syncthreads();
  DBG_S(7);
  return pack_params(pnext);
}

__global__ void __cluster_dims__(2, 1, 1) __launch_bounds__(512, 1)
fused_kernel(const __grid_constant__ CUtensorMap tm_x, const __grid_constant__ CUtensorMap tm_w1,
             const __grid_constant__ CUtensorMap tm_w2, const __grid_constant__ CUtensorMap tm_aT,
             const __grid_constant__ CUtensorMap tm_xn, const __grid_constant__ CUtensorMap tm_out,
             const __grid_constant__ CUtensorMap tm_a8,
             const __grid_constant__ Args ar, const __grid_constant__ Scratch sc) {
  extern __shared__ __align__(1024) char smem_raw[];
  DBG_G(28);
  const uint32_t sb = (smem_u32(smem_raw) + 1023) & ~1023u;
  char* sm = smem_raw + (sb - smem_u32(smem_raw));
  const uint32_t bars = sb + OFF_BAR;
  const int tid = threadIdx.x, lane = tid & 31;
  const int warp = __shfl_sync(0xffffffffu, tid >> 5, 0), wg = warp >> 2;
  const int bid = blockIdx.x;
  const int m = bid >> 3, f = bid & 7, rank = f & 1, pr = f >> 1;

  const int dbase = bid < 128 ? bid * 4 : 512 + (bid - 128) * 16;
  uint32_t praw[8];
  load_params(praw, ar, dbase + wg, tid & 127);

  if (lane == 0) {
    if (warp == 8) {
#pragma unroll
      for (int i = 0; i < B_EMPTY / 8; i++) mbar_init(bars + i * 8, 1);
      asm volatile("fence.mbarrier_init.release.cluster;" ::: "memory");
#pragma unroll
      for (int i = 0; i < 4; i++) mbar_expect_tx(bars + B_RB + 8 * i, 16384);
    } else if (warp == 9) {
#pragma unroll
      for (int i = B_EMPTY / 8; i < NBARS; i++) mbar_init(bars + i * 8, 8);
      asm volatile("fence.mbarrier_init.release.cluster;" ::: "memory");
    } else if (warp == 10) {
      asm volatile("prefetch.tensormap [%0];" ::"l"(&tm_x) : "memory");
    } else if (warp == 11) {
      *reinterpret_cast<Args*>(sm + OFF_ARGS) = ar;
      *reinterpret_cast<Scratch*>(sm + OFF_ARGS + 128) = sc;
    }
  }
  __syncthreads();
  asm volatile("barrier.cluster.arrive.relaxed.aligned;" ::: "memory");

  {
    Maps tm;
    tm.x = &tm_x; tm.w1 = &tm_w1; tm.xn = &tm_xn;
    const int npass = bid < 128 ? 1 : 4;
    if (lane == 0 && (warp & 1) == 0) {
      mbar_expect_tx(bars + B_U, 4096);
      tma2d(sb + xg_off(warp >> 1), &tm_x, dbase & ~7, (warp >> 1) * 256, bars + B_U);
    }
    {
      char* eb = sm + e_off(wg);
      const int n = tid & 127;
      const uint4 z = make_uint4(0, 0, 0, 0);
      SM_U4(eb + E_TAP + n * 16) = z;
      if (n < 104) SM_U4(eb + E_TAP + 2048 + n * 16) = z;
      else if (n == 104) SM_U4(eb + E_W9) = z;
      if (n < 33) SM_U4(sm + l_off(wg) + n * 16) = z;
    }
    uint4 pv = pack_params(praw);
#pragma unroll 1
    for (int pass = 0; pass < npass; pass++)
      pv = ssm_pass(tm, sm, dbase + pass * 4, pass, pv
      );
  }
  if (bid >= 128) {
    if (tid == 0) {
      asm volatile("fence.acq_rel.gpu;" ::: "memory");
      atomicAdd(&sc.flags[304], 1u);
    }
    __syncwarp();
    asm volatile("barrier.cluster.wait.acquire.aligned;" ::: "memory");
    return;
  }

  const uint32_t rdelta = mapa(sb, rank ^ 1) - sb;
  if (wg >= 2) {
    asm volatile("setmaxnreg.dec.sync.aligned.u32 24;");
    asm volatile("barrier.cluster.wait.acquire.aligned;" ::: "memory");
    const int pw = warp - 8;
    if (lane == 0) {
      if (pw < 2) {
        int slot = pw, par = 0;
#pragma unroll 1
        for (int it = 6 + pw; it < 54; it += 2) {
          const int ch = it / 9, s = it - ch * 9;
          const uint32_t fb = bars + B_FULL + 8 * slot;
          mbar_wait(bars + B_EMPTY + 8 * slot, par);
          mbar_expect_tx(fb, STAGE_BYTES);
          tma3d(sb + OFF_ST + slot * STAGE_BYTES, &tm_w1, 0, s * 64, f * 18 + ch * 3, fb);
          slot += 2;
          if (slot >= 6) { slot -= 6; par ^= 1; }
        }
#pragma unroll 1
        for (int pos = 0; pos < 9; pos++) {
          const int chunk = chunk_of(pos, pr, rank);
#pragma unroll 1
          for (slot = pw; slot < 6; slot += 2) {
            const uint32_t fb = bars + B_FULL + 8 * slot;
            mbar_wait(bars + B_EMPTY + 8 * slot, par);
            mbar_expect_tx(fb, STAGE_BYTES);
            tma2d(sb + OFF_ST + slot * STAGE_BYTES, &tm_w2, chunk * 64, f * 576 + slot * 96, fb);
          }
          par ^= 1;
        }
        if (pw == 0) {
          wait_flag(&sc.flags[288 + f * 2], 16);
          mbar_wait(bars + B_EMPTY, par);
          mbar_wait(bars + B_EMPTY + 8, par);
          mbar_expect_tx(bars + B_FULL, 16384);
          tma2d(sb + OFF_ST, &tm_aT, m * 128, f * 64, bars + B_FULL);
          tma2d(sb + OFF_ST + 8192, &tm_aT, m * 128 + 64, f * 64, bars + B_FULL);
          if (atomicAdd(&sc.flags[289 + f * 2], 1u) == 15) { sc.flags[288 + f * 2] = 0; sc.flags[289 + f * 2] = 0; }
        }
      } else if (pw == 2) {
        mbar_wait(bars + B_P1R, 0);
#pragma unroll 1
        for (int k = 0; k < 4; k++) {
          mbar_wait(bars + B_TS + 8 * k, 0);
          HFENCE();
          bulk_s2peer(sb + k * 16384 + rdelta, sb + OFF_STG + k * 16384, 16384, bars + B_RB + 8 * k + rdelta);
        }
#pragma unroll 1
        for (int k = 0; k < 4; k++) mbar_wait(bars + B_RB + 8 * k, 0);
        mbar_arrive_remote(bars + B_FIN + rdelta);
        mbar_wait(bars + B_FIN, 0);
      } else if (pw == 3) {
        mbar_wait(bars + B_TS8, 0);
        HFENCE();
        bulk_s2g_release(sc.slots8 + (size_t)(m * 8 + f) * 4096, sb + OFF_C8, 16384);
#pragma unroll 1
        for (int i = 0; i < 8; i++) atomicAdd(&sc.flags[m * 16 + 8 + i], 1u);
#pragma unroll 1
        for (int k = 0; k < 3; k++) {
          const int chunk = 2 * ((pr + k + 1) & 3) + rank;
          mbar_wait(bars + B_TR + 8 * k, 0);
          HFENCE();
          bulk_s2g_release(sc.slots + (size_t)((m * 8 + chunk) * 3 + k) * 4096, sb + k * 16384, 16384);
          atomicAdd(&sc.flags[320 + (m * 8 + chunk) * 4 + k], 1u);
          DBG_H(16 + k);
          if (k == 0) {
            mbar_expect_tx(bars + B_OWN, 65536);
            wait_flag(&sc.flags[m * 16 + 8 + f], 8);
            sc.flags[m * 16 + 8 + f] = 0;
#pragma unroll 1
            for (int i = 0; i < 8; i++)
              bulk_g2s(sb + OFF_C8 + i * 2048, sc.slots8 + (size_t)(m * 8 + i) * 4096 + f * 512, 2048, bars + B_OWN);
          }
#pragma unroll 1
          for (int j = k - 1; j >= 0 && j <= k; j += (k == 2 ? 1 : 2)) {
            unsigned int* fl = &sc.flags[320 + (m * 8 + f) * 4 + j];
            wait_flag(fl, 1);
            *fl = 0;
            bulk_g2s(sb + j * 16384, sc.slots + (size_t)((m * 8 + f) * 3 + j) * 4096, 16384, bars + B_OWN);
          }
        }
        if (f == 0) sc.flags[256 + m] = 0;
        DBG_H(19);
      } else if (pw == 4) {
        asm volatile("fence.acq_rel.gpu;" ::: "memory");
        atomicAdd(&sc.flags[288 + (bid >> 4) * 2], 1u);
        mbar_wait(bars + B_TR + 8, 0);
        wait_flag(&sc.flags[304], 4);
        mbar_expect_tx(bars + B_A8, 2048);
        tma2d(sb + OFF_A8, &tm_a8, m * 128, 512 + f * 8, bars + B_A8);
        if (atomicAdd(&sc.flags[305], 1u) == 127) { sc.flags[304] = 0; sc.flags[305] = 0; }
      } else {
        HFENCE();
#pragma unroll 1
        for (int kb = pw - 3; kb < 9; kb += 3) {
          mbar_expect_tx(bars + B_X + 8 * kb, kb == 8 ? 16384 + 2304 : 16384);
          tma2d(sb + kb * 16384, &tm_xn, kb * 64, m * 128, bars + B_X + 8 * kb);
          if (kb == 8) {
            bulk_g2s(sb + OFF_B1, ar.b1 + f * 576, 1152, bars + B_X + 64);
            bulk_g2s(sb + OFF_B2, ar.b2, 1152, bars + B_X + 64);
          }
        }
      }
    }
  } else {
    asm volatile("setmaxnreg.inc.sync.aligned.u32 232;");
    const int wi = warp & 3;
    DBG_T(0);
    MlpCtx c;
    c.bars = bars; c.lane = lane;
    c.dA = (((sb + wg * 8192) & 0x3FFFF) >> 4) | (1u << 16);
    c.dB = ((sb + OFF_ST) & 0x3FFFF) >> 4;

    uint32_t h[144];
    float acc2a[32], acc2b[32];
    {
      float accA[48], accB[48];
#pragma unroll
      for (int i = 0; i < 48; i++) { accA[i] = 0.f; accB[i] = 0.f; }
#pragma unroll
      for (int i = 0; i < 144; i++) h[i] = 0;
      uint32_t baddr = sb + OFF_B1 + (lane & 3) * 4 - 192;
#pragma unroll 1
      for (int j = 0; j < 3; j++) {
        DBG_T(11 + 2 * j);
        p1_chunk<0>(c, j, baddr, accA, accB, h);
        baddr += 192;
        DBG_T(10 + 2 * j);
        p1_chunk<9>(c, j, baddr, accB, accA, h);
        baddr += 192;
      }
      DBG_T(2);
      p2_mma<0>(c, 1, acc2a, h);
      wg_wait<1>();
      stage_release(c, 5);
      fence_regs(accB);
      asm volatile("barrier.cluster.wait.acquire.aligned;" ::: "memory");
      if (lane == 0) { mbar_arrive(bars + B_P1L); mbar_arrive_remote(bars + B_P1R + rdelta); }
      p2_mma<1>(c, 1, acc2a, h);
      gelu_part<0>(baddr, accB); gelu_part<1>(baddr, accB);
      wg_wait<1>(); stage_release(c, 0);
      p2_mma<2>(c, 1, acc2a, h);
      gelu_part<2>(baddr, accB); gelu_part<3>(baddr, accB);
      wg_wait<1>(); stage_release(c, 1);
      p2_mma<3>(c, 1, acc2a, h);
      gelu_part<4>(baddr, accB);
      wg_wait<1>(); stage_release(c, 2);
      p2_mma<4>(c, 1, acc2a, h);
      gelu_part<5>(baddr, accB);
#pragma unroll
      for (int i = 0; i < 24; i++) h[120 + i] = __float_as_uint(accB[(i >> 2) * 8 + (i & 3)]);
      wg_wait<1>(); stage_release(c, 3);
      p2_mma<5>(c, 1, acc2a, h);
      wg_wait<1>(); stage_release(c, 4);
    }
    const uint32_t lbuf = sb + warp * 2048 + lane * 16;
    mbar_wait(bars + B_P1L, 0);
#pragma unroll 1
    for (int pos = 0; pos < 8; pos++) {
      const bool recv = (0x68 >> pos) & 1;
      const int k = recv ? (pos - 2) >> 1 : (pos + 1) >> 1;
      const int ks = k > 3 ? 3 : k;
      const uint32_t addr = lbuf + ks * 16384 + (recv ? 0 : OFF_STG);
      const uint32_t sig = bars + (recv ? B_TR + 8 * k : pos == 1 ? B_TS8 : B_TS + 8 * ks);
      if (recv) mbar_wait(bars + B_RB + k * 8, 0);
      wg_wait<0>(); stage_release(c, 5);
      fence_regs(acc2a);
      DBG_T(20 + pos);
      if (recv) {
#pragma unroll
        for (int i = 0; i < 4; i++) {
          const float4 r = lds128f(addr + i * 512);
          const uint32_t w0 = __float_as_uint(r.x), w1 = __float_as_uint(r.y), w2 = __float_as_uint(r.z), w3 = __float_as_uint(r.w);
          acc2a[8 * i + 0] += bf_lo(w0); acc2a[8 * i + 1] += bf_hi(w0); acc2a[8 * i + 2] += bf_lo(w1); acc2a[8 * i + 3] += bf_hi(w1);
          acc2a[8 * i + 4] += bf_lo(w2); acc2a[8 * i + 5] += bf_hi(w2); acc2a[8 * i + 6] += bf_lo(w3); acc2a[8 * i + 7] += bf_hi(w3);
        }
      }
      if (pos == 1) {
        const uint32_t a8 = sb + OFF_C8 + warp * 256 + lane * 8;
#pragma unroll
        for (int q = 0; q < 8; q++)
          asm volatile("st.shared.v2.u32 [%0], {%1,%2};" ::"r"(a8 + q * 2048), "r"(pack_bf16(acc2a[4 * q], acc2a[4 * q + 1])),
                       "r"(pack_bf16(acc2a[4 * q + 2], acc2a[4 * q + 3])) : "memory");
      } else {
#pragma unroll
        for (int i = 0; i < 4; i++)
          sts128(addr + i * 512, pack_bf16(acc2a[8 * i], acc2a[8 * i + 1]), pack_bf16(acc2a[8 * i + 2], acc2a[8 * i + 3]),
                 pack_bf16(acc2a[8 * i + 4], acc2a[8 * i + 5]), pack_bf16(acc2a[8 * i + 6], acc2a[8 * i + 7]));
      }
      const uint32_t par = pos & 1;
      p2_mma<0>(c, par, acc2a, h);
      __syncwarp();
      if (lane == 0) mbar_arrive(sig);
      p2_mma<1>(c, par, acc2a, h);
      wg_wait<1>(); stage_release(c, 0);
      p2_mma<2>(c, par, acc2a, h);
      wg_wait<1>(); stage_release(c, 1);
      p2_mma<3>(c, par, acc2a, h);
      wg_wait<1>(); stage_release(c, 2);
      p2_mma<4>(c, par, acc2a, h);
      wg_wait<1>(); stage_release(c, 3);
      p2_mma<5>(c, par, acc2a, h);
      wg_wait<1>(); stage_release(c, 4);
    }
    DBG_T(3);
    {
      const int g = lane >> 2, cc = lane & 3;
      const int t0 = m * 128 + warp * 16 + g;
      const uint2 ga = __ldcg(&sc.gate[t0]), gb = __ldcg(&sc.gate[t0 + 8]);
#pragma unroll
      for (int i = 0; i < 32; i++) acc2b[i] = 0.f;
      mbar_wait(bars + B_RB + 24, 0);
      mbar_wait(bars + B_OWN, 0);
      DBG_T(8);
#pragma unroll
      for (int k = 0; k < 4; k++) {
#pragma unroll
        for (int i = 0; i < 4; i++) {
          float4 r = lds128f(lbuf + k * 16384 + i * 512);
          const uint32_t w0 = __float_as_uint(r.x), w1 = __float_as_uint(r.y), w2 = __float_as_uint(r.z), w3 = __float_as_uint(r.w);
          acc2b[8 * i + 0] += bf_lo(w0); acc2b[8 * i + 1] += bf_hi(w0); acc2b[8 * i + 2] += bf_lo(w1); acc2b[8 * i + 3] += bf_hi(w1);
          acc2b[8 * i + 4] += bf_lo(w2); acc2b[8 * i + 5] += bf_hi(w2); acc2b[8 * i + 6] += bf_lo(w3); acc2b[8 * i + 7] += bf_hi(w3);
        }
      }
      float c8[4] = {0.f, 0.f, 0.f, 0.f};
#pragma unroll
      for (int i = 0; i < 8; i++) {
        uint32_t w0, w1;
        asm volatile("ld.shared.v2.u32 {%0,%1}, [%2];" : "=r"(w0), "=r"(w1) : "r"(sb + OFF_C8 + i * 2048 + warp * 256 + lane * 8));
        c8[0] += bf_lo(w0); c8[1] += bf_hi(w0); c8[2] += bf_lo(w1); c8[3] += bf_hi(w1);
      }
      DBG_T(9);
      mbar_wait(bars + B_FULL, 0);
      wg_wait<0>();
      fence_regs(acc2a);
      DBG_T(4);
#pragma unroll
      for (int jj = 0; jj < 4; jj++) {
        uint32_t a[4];
        {
          const int dl = 8 * (2 * jj + (lane >> 4)) + (lane & 7);
          const int chk = 2 * wi + ((lane >> 3) & 1);
          ldsm4t(a, sb + OFF_ST + wg * 8192 + dl * 128 + ((chk ^ (dl & 7)) << 4));
        }
        uint32_t o[4];
#pragma unroll
        for (int e = 0; e < 2; e++) {
          const int q = 2 * jj + e;
          uint32_t bb = lds32(sb + OFF_B2 + (f * 64 + q * 8 + cc * 2) * 2);
          uint32_t v0 = bf2_add(pack_bf16(acc2a[4 * q] + acc2b[4 * q], acc2a[4 * q + 1] + acc2b[4 * q + 1]), bb);
          uint32_t v1 = bf2_add(pack_bf16(acc2a[4 * q + 2] + acc2b[4 * q + 2], acc2a[4 * q + 3] + acc2b[4 * q + 3]), bb);
          o[2 * e] = bf2_add(bf2_mul(ga.x, a[2 * e]), bf2_mul(ga.y, v0));
          o[2 * e + 1] = bf2_add(bf2_mul(gb.x, a[2 * e + 1]), bf2_mul(gb.y, v1));
        }
        {
          const int row = (lane & 7) + ((lane >> 3) & 1) * 8;
          const uint32_t addr = sb + 49152 + warp * 2048 + row * 128 + (((2 * jj + (lane >> 4)) ^ (row & 7)) << 4);
          asm volatile("stmatrix.sync.aligned.m8n8.x4.shared.b16 [%0], {%1,%2,%3,%4};"
                       ::"r"(addr), "r"(o[0]), "r"(o[1]), "r"(o[2]), "r"(o[3]) : "memory");
        }
      }
      asm volatile("fence.proxy.async.shared::cta;" ::: "memory");
      __syncwarp();
      if (lane == 0) {
        asm volatile("cp.async.bulk.tensor.2d.global.shared::cta.bulk_group [%0, {%2, %3}], [%1];\n"
                     "cp.async.bulk.commit_group;"
                     ::"l"(&tm_out), "r"(sb + 49152 + warp * 2048), "r"(f * 64), "r"(m * 128 + warp * 16) : "memory");
      }
      __syncwarp();
      mbar_wait(bars + B_A8, 0);
      {
        __nv_bfloat16* op = ar.out + (size_t)t0 * D_MOD + cc * 2 + 512 + f * 8;
        uint32_t a0, a1;
        const uint32_t addr = sb + OFF_A8 + (lane & 7) * 256 + (warp * 2 + ((lane >> 3) & 1)) * 16;
        asm volatile("ldmatrix.sync.aligned.m8n8.x2.trans.shared.b16 {%0,%1}, [%2];" : "=r"(a0), "=r"(a1) : "r"(addr));
        const uint32_t bb = lds32(sb + OFF_B2 + (512 + f * 8 + cc * 2) * 2);
        const uint32_t v0 = bf2_add(pack_bf16(c8[0], c8[1]), bb), v1 = bf2_add(pack_bf16(c8[2], c8[3]), bb);
        *reinterpret_cast<uint32_t*>(op) = bf2_add(bf2_mul(ga.x, a0), bf2_mul(ga.y, v0));
        *reinterpret_cast<uint32_t*>(op + 8 * D_MOD) = bf2_add(bf2_mul(gb.x, a1), bf2_mul(gb.y, v1));
      }
      if (lane == 0) asm volatile("cp.async.bulk.wait_group.read 0;" ::: "memory");
      DBG_T(5);
      DBG_G(29);
    }
  }
}

typedef CUresult (*EncodeTiledFn)(CUtensorMap*, CUtensorMapDataType, cuuint32_t, void*, const cuuint64_t*,
                                  const cuuint64_t*, const cuuint32_t*, const cuuint32_t*, CUtensorMapInterleave,
                                  CUtensorMapSwizzle, CUtensorMapL2promotion, CUtensorMapFloatOOBfill);

static void make_map(EncodeTiledFn enc, CUtensorMap* tm, const void* base, uint64_t inner, uint64_t outer, uint32_t binner,
                     uint32_t bouter, CUtensorMapSwizzle swz) {
  cuuint64_t gd[2] = {inner, outer};
  cuuint64_t gs[1] = {inner * 2};
  cuuint32_t bd[2] = {binner, bouter};
  cuuint32_t es[2] = {1, 1};
  enc(tm, CU_TENSOR_MAP_DATA_TYPE_BFLOAT16, 2, const_cast<void*>(base), gd, gs, bd, es, CU_TENSOR_MAP_INTERLEAVE_NONE, swz,
      CU_TENSOR_MAP_L2_PROMOTION_L2_128B, CU_TENSOR_MAP_FLOAT_OOB_FILL_NONE);
}

extern "C" void kernel_launch(void* const* d_in, const int* in_sizes, int n_in, void* d_out, int out_size) {
  typedef const __nv_bfloat16* BP;
  Args ar;
  ar.u = (BP)d_in[0]; ar.Are = (BP)d_in[1]; ar.Aim = (BP)d_in[2]; ar.Bre = (BP)d_in[3]; ar.Bim = (BP)d_in[4];
  ar.Cre = (BP)d_in[5]; ar.Cim = (BP)d_in[6]; ar.logdt = (BP)d_in[7]; ar.Dskip = (BP)d_in[8];
  ar.w1 = (BP)d_in[10]; ar.b1 = (BP)d_in[11]; ar.w2 = (BP)d_in[12]; ar.b2 = (BP)d_in[13]; ar.gate_w = (BP)d_in[14];
  ar.out = (__nv_bfloat16*)d_out;

  static EncodeTiledFn enc = nullptr;
  static Scratch sc;
  if (!enc) {
    cudaDriverEntryPointQueryResult qr;
    cudaGetDriverEntryPoint("cuTensorMapEncodeTiled", (void**)&enc, cudaEnableDefault, &qr);
    cudaGetSymbolAddress((void**)&sc.aT, g_aT);
    cudaGetSymbolAddress((void**)&sc.xn, g_xn);
    cudaGetSymbolAddress((void**)&sc.gate, g_gate);
    cudaGetSymbolAddress((void**)&sc.slots, g_slots);
    cudaGetSymbolAddress((void**)&sc.slots8, g_slots8);
    cudaGetSymbolAddress((void**)&sc.flags, g_flags);
    sc.dbg = nullptr;
    cudaFuncSetAttribute(fused_kernel, cudaFuncAttributeMaxDynamicSharedMemorySize, SMEM_BYTES);
  }
  CUtensorMap tm_x, tm_w1, tm_w2, tm_aT, tm_xn, tm_out, tm_a8;
  make_map(enc, &tm_a8, sc.aT, L_SEQ, D_MOD, 128, 8, CU_TENSOR_MAP_SWIZZLE_NONE);
  make_map(enc, &tm_x, ar.u, D_MOD, L_SEQ, 8, 256, CU_TENSOR_MAP_SWIZZLE_NONE);
  make_map(enc, &tm_w2, ar.w2, D_MOD, F_HID, 64, 96, CU_TENSOR_MAP_SWIZZLE_128B);
  make_map(enc, &tm_aT, sc.aT, L_SEQ, D_MOD, 64, 64, CU_TENSOR_MAP_SWIZZLE_128B);
  make_map(enc, &tm_xn, sc.xn, D_MOD, L_SEQ, 64, 128, CU_TENSOR_MAP_SWIZZLE_128B);
  make_map(enc, &tm_out, d_out, D_MOD, L_SEQ, 64, 16, CU_TENSOR_MAP_SWIZZLE_128B);
  {
    cuuint64_t gd[3] = {32, D_MOD, F_HID / 32};
    cuuint64_t gs[2] = {F_HID * 2, 64};
    cuuint32_t bd[3] = {32, 64, 3};
    cuuint32_t es[3] = {1, 1, 1};
    enc(&tm_w1, CU_TENSOR_MAP_DATA_TYPE_BFLOAT16, 3, (void*)ar.w1, gd, gs, bd, es, CU_TENSOR_MAP_INTERLEAVE_NONE,
        CU_TENSOR_MAP_SWIZZLE_64B, CU_TENSOR_MAP_L2_PROMOTION_L2_128B, CU_TENSOR_MAP_FLOAT_OOB_FILL_NONE);
  }
  fused_kernel<<<132, 512, SMEM_BYTES, cudaStreamPerThread>>>(tm_x, tm_w1, tm_w2, tm_aT, tm_xn, tm_out, tm_a8, ar, sc);
}
```

```cpp
#include <cuda_runtime.h>
#include <cuda_bf16.h>
#include <cuda.h>
#include <stdint.h>

#define HFENCE() asm volatile("fence.proxy.async.shared::cta;" ::: "memory")
#define L_SEQ 2048
#define D_MOD 576
#define F_HID 4608
#define N_ST 128

__device__ __align__(1024) __nv_bfloat16 g_aT[D_MOD * L_SEQ];
__device__ __align__(1024) __nv_bfloat16 g_xn[L_SEQ * D_MOD];
__device__ __align__(1024) uint32_t g_slots[16 * 8 * 3 * 4096];
__device__ __align__(1024) uint32_t g_slots8[16 * 8 * 4096];
__device__ uint2 g_gate[L_SEQ];
__device__ unsigned int g_flags[832];
struct Scratch {
  __nv_bfloat16* aT; __nv_bfloat16* xn; uint2* gate; uint32_t* slots; uint32_t* slots8; unsigned int* flags;
  long long* dbg;
};
#define DBG_T(i)
#define DBG_S(i)
#define DBG_H(i)
#define DBG_G(i)

__device__ __forceinline__ uint32_t smem_u32(const void* p) { return (uint32_t)__cvta_generic_to_shared(p); }
__device__ __forceinline__ void mbar_init(uint32_t bar, int cnt) {
  asm volatile("mbarrier.init.shared::cta.b64 [%0], %1;" ::"r"(bar), "r"(cnt));
}
__device__ __forceinline__ void mbar_expect_tx(uint32_t bar, uint32_t bytes) {
  asm volatile("mbarrier.arrive.expect_tx.shared::cta.b64 _, [%0], %1;" ::"r"(bar), "r"(bytes) : "memory");
}
__device__ __forceinline__ void mbar_arrive(uint32_t bar) {
  asm volatile("mbarrier.arrive.shared::cta.b64 _, [%0];" ::"r"(bar) : "memory");
}
__device__ __forceinline__ void mbar_arrive_remote(uint32_t remote_bar) {
  asm volatile("mbarrier.arrive.relaxed.cluster.shared::cluster.b64 _, [%0];" ::"r"(remote_bar) : "memory");
}
__device__ __forceinline__ void mbar_wait(uint32_t bar, uint32_t parity) {
  asm volatile(
      "{\n.reg .pred p;\n.reg .u32 n;\nmov.u32 n, 0;\n"
      "W_%=:\nmbarrier.try_wait.parity.shared::cta.b64 p, [%0], %1;\n@p bra D_%=;\n"
      "add.u32 n, n, 1;\nsetp.lt.u32 p, n, 400000;\n@p bra W_%=;\ntrap;\nD_%=:\n}"
      ::"r"(bar), "r"(parity) : "memory");
}
__device__ __forceinline__ void tma2d(uint32_t dst, const CUtensorMap* tm, int c0, int c1, uint32_t bar) {
  asm volatile("cp.async.bulk.tensor.2d.shared::cluster.global.mbarrier::complete_tx::bytes [%0], [%1, {%3, %4}], [%2];"
               ::"r"(dst), "l"(tm), "r"(bar), "r"(c0), "r"(c1) : "memory");
}
__device__ __forceinline__ void wait_flag(unsigned int* flag, unsigned int target) {
  asm volatile(
      "{\n.reg .pred p;\n.reg .u32 n, v;\nmov.u32 n, 0;\n"
      "W_%=:\nld.acquire.gpu.global.u32 v, [%0];\nsetp.ge.u32 p, v, %1;\n@p bra D_%=;\n"
      "nanosleep.u32 32;\nadd.u32 n, n, 1;\nsetp.lt.u32 p, n, 4000000;\n@p bra W_%=;\ntrap;\nD_%=:\n}"
      ::"l"(flag), "r"(target) : "memory");
}
__device__ __forceinline__ void bulk_g2s(uint32_t dst, const void* src, uint32_t bytes, uint32_t bar) {
  asm volatile("cp.async.bulk.shared::cluster.global.mbarrier::complete_tx::bytes [%0], [%1], %2, [%3];"
               ::"r"(dst), "l"(src), "r"(bytes), "r"(bar) : "memory");
}
__device__ __forceinline__ void tma3d(uint32_t dst, const CUtensorMap* tm, int c0, int c1, int c2, uint32_t bar) {
  asm volatile("cp.async.bulk.tensor.3d.shared::cluster.global.mbarrier::complete_tx::bytes [%0], [%1, {%3, %4, %5}], [%2];"
               ::"r"(dst), "l"(tm), "r"(bar), "r"(c0), "r"(c1), "r"(c2) : "memory");
}
__device__ __forceinline__ uint32_t mapa(uint32_t addr, uint32_t rank) {
  uint32_t r;
  asm("mapa.shared::cluster.u32 %0, %1, %2;" : "=r"(r) : "r"(addr), "r"(rank));
  return r;
}
__device__ __forceinline__ float4 lds128f(uint32_t addr) {
  float4 v;
  asm volatile("ld.shared.v4.f32 {%0,%1,%2,%3}, [%4];" : "=f"(v.x), "=f"(v.y), "=f"(v.z), "=f"(v.w) : "r"(addr));
  return v;
}
__device__ __forceinline__ uint32_t lds32(uint32_t addr) {
  uint32_t v;
  asm volatile("ld.shared.u32 %0, [%1];" : "=r"(v) : "r"(addr));
  return v;
}
__device__ __forceinline__ void sts128(uint32_t addr, uint32_t a, uint32_t b, uint32_t c, uint32_t d) {
  asm volatile("st.shared.v4.u32 [%0], {%1,%2,%3,%4};" ::"r"(addr), "r"(a), "r"(b), "r"(c), "r"(d) : "memory");
}
#define WG_FENCE() asm volatile("wgmma.fence.sync.aligned;" ::: "memory")
#define WG_COMMIT() asm volatile("wgmma.commit_group.sync.aligned;" ::: "memory")
template <int n> __device__ __forceinline__ void wg_wait() {
  asm volatile("wgmma.wait_group.sync.aligned %0;" ::"n"(n) : "memory");
}
__device__ __forceinline__ uint32_t pack_bf16(float lo, float hi) {
  uint32_t r;
  asm("cvt.rn.bf16x2.f32 %0, %1, %2;" : "=r"(r) : "f"(hi), "f"(lo));
  return r;
}
__device__ __forceinline__ float bf_lo(uint32_t p) { return __uint_as_float(p << 16); }
__device__ __forceinline__ float bf_hi(uint32_t p) { return __uint_as_float(p & 0xffff0000u); }
__device__ __forceinline__ float bf_round(float x) { return __bfloat162float(__float2bfloat16_rn(x)); }
__device__ __forceinline__ uint32_t bf2_add(uint32_t a, uint32_t b) {
  uint32_t r;
  asm("add.rn.bf16x2 %0, %1, %2;" : "=r"(r) : "r"(a), "r"(b));
  return r;
}
__device__ __forceinline__ uint32_t bf2_mul(uint32_t a, uint32_t b) {
  uint32_t r;
  asm("mul.rn.bf16x2 %0, %1, %2;" : "=r"(r) : "r"(a), "r"(b));
  return r;
}
__device__ __forceinline__ uint32_t bf2_fma(uint32_t a, uint32_t b, uint32_t c) {
  uint32_t r;
  asm("fma.rn.bf16x2 %0, %1, %2, %3;" : "=r"(r) : "r"(a), "r"(b), "r"(c));
  return r;
}
__device__ __forceinline__ uint32_t gelu_pack(float a0, float a1, uint32_t hbias2) {
  const uint32_t hp = bf2_fma(pack_bf16(a0, a1), 0x3f003f00u, hbias2);
  const uint32_t q = bf2_fma(bf2_mul(hp, hp), 0x3e923e92u  , 0x3fcc3fccu  );
  uint32_t t;
  asm("tanh.approx.bf16x2 %0, %1;" : "=r"(t) : "r"(bf2_mul(hp, q)));
  return bf2_fma(hp, t, hp);
}

#define R8(a, o) "+f"(a[o]), "+f"(a[o + 1]), "+f"(a[o + 2]), "+f"(a[o + 3]), "+f"(a[o + 4]), "+f"(a[o + 5]), "+f"(a[o + 6]), "+f"(a[o + 7])
#define W8(a, o) "=f"(a[o]), "=f"(a[o + 1]), "=f"(a[o + 2]), "=f"(a[o + 3]), "=f"(a[o + 4]), "=f"(a[o + 5]), "=f"(a[o + 6]), "=f"(a[o + 7])
#define REGS48 "{%0,%1,%2,%3,%4,%5,%6,%7,%8,%9,%10,%11,%12,%13,%14,%15,%16,%17,%18,%19,%20,%21,%22,%23," \
               "%24,%25,%26,%27,%28,%29,%30,%31,%32,%33,%34,%35,%36,%37,%38,%39,%40,%41,%42,%43,%44,%45,%46,%47}"
#define REGS32 "{%0,%1,%2,%3,%4,%5,%6,%7,%8,%9,%10,%11,%12,%13,%14,%15,%16,%17,%18,%19,%20,%21,%22,%23," \
               "%24,%25,%26,%27,%28,%29,%30,%31}"
#define DESC_HI_A  "0x40000040"
#define DESC_HI_B1 "0x80000020"
#define DESC_HI_B2 "0x40000040"
template <bool ACC, int OA, int OB>
__device__ __forceinline__ void wgmma_ss_n96(float (&d)[48], uint32_t da, uint32_t db) {
  if (ACC)
    asm volatile("{\n.reg .b64 xa, xb;\n.reg .b32 la, lb;\nadd.u32 la, %48, %50;\nadd.u32 lb, %49, %51;\n"
                 "mov.b64 xa, {la, " DESC_HI_A "};\nmov.b64 xb, {lb, " DESC_HI_B1 "};\n"
                 "wgmma.mma_async.sync.aligned.m64n96k16.f32.bf16.bf16 " REGS48 ", xa, xb, 1, 1, 1, 0, 1;\n}\n"
                 : R8(d, 0), R8(d, 8), R8(d, 16), R8(d, 24), R8(d, 32), R8(d, 40) : "r"(da), "r"(db), "n"(OA), "n"(OB));
  else
    asm volatile("{\n.reg .b64 xa, xb;\n.reg .b32 la, lb;\nadd.u32 la, %48, %50;\nadd.u32 lb, %49, %51;\n"
                 "mov.b64 xa, {la, " DESC_HI_A "};\nmov.b64 xb, {lb, " DESC_HI_B1 "};\n"
                 "wgmma.mma_async.sync.aligned.m64n96k16.f32.bf16.bf16 " REGS48 ", xa, xb, 0, 1, 1, 0, 1;\n}\n"
                 : W8(d, 0), W8(d, 8), W8(d, 16), W8(d, 24), W8(d, 32), W8(d, 40) : "r"(da), "r"(db), "n"(OA), "n"(OB));
}
template <bool ACC, int OB>
__device__ __forceinline__ void wgmma_rs_n64(float (&d)[32], uint32_t a0, uint32_t a1, uint32_t a2, uint32_t a3, uint32_t db) {
  if (ACC)
    asm volatile("{\n.reg .b64 xb;\n.reg .b32 lb;\nadd.u32 lb, %36, %37;\nmov.b64 xb, {lb, " DESC_HI_B2 "};\n"
                 "wgmma.mma_async.sync.aligned.m64n64k16.f32.bf16.bf16 " REGS32 ", {%32,%33,%34,%35}, xb, 1, 1, 1, 1;\n}\n"
                 : R8(d, 0), R8(d, 8), R8(d, 16), R8(d, 24) : "r"(a0), "r"(a1), "r"(a2), "r"(a3), "r"(db), "n"(OB));
  else
    asm volatile("{\n.reg .b64 xb;\n.reg .b32 lb;\nadd.u32 lb, %36, %37;\nmov.b64 xb, {lb, " DESC_HI_B2 "};\n"
                 "wgmma.mma_async.sync.aligned.m64n64k16.f32.bf16.bf16 " REGS32 ", {%32,%33,%34,%35}, xb, 0, 1, 1, 1;\n}\n"
                 : W8(d, 0), W8(d, 8), W8(d, 16), W8(d, 24) : "r"(a0), "r"(a1), "r"(a2), "r"(a3), "r"(db), "n"(OB));
}
template <int N> __device__ __forceinline__ void fence_regs(float (&d)[N]) {
#pragma unroll
  for (int i = 0; i < N; i++) asm volatile("" : "+f"(d[i])::"memory");
}

constexpr int XS_BYTES = 9 * 16384;
constexpr int STAGE_BYTES = 12288;
constexpr int OFF_ST = XS_BYTES;
constexpr int OFF_B1 = OFF_ST + 6 * STAGE_BYTES;
constexpr int OFF_B2 = OFF_B1 + 1152;
constexpr int OFF_BAR = OFF_B2 + 1152;
constexpr int B_FULL = 0, B_X = 48  , B_RB = 120  , B_OWN = 152, B_FIN = 160, B_A8 = 168,
              B_EMPTY = 176  , B_TS = 224  , B_TS8 = 256, B_TR = 264  , B_P1L = 288, B_P1R = 296, B_U = 304,
              B_U0 = 312, NBARS = 40,
              B_CONV = 320, B_COMB = 328;
constexpr int OFF_A8 = OFF_BAR + 512;
constexpr int OFF_ARGS = OFF_A8 + 2048;
constexpr int SMEM_BYTES = OFF_ARGS + 256 + 1024;
constexpr int OFF_STG = 65536, OFF_C8 = 131072;
constexpr int E_UA = 0, E_UB = 3616, E_W3A = 7232, E_W3B = 10848, E_W5 = 14464, E_W9 = 17568, E_TAP = 19680, E_SIZE = 23392;
constexpr int L_W7 = 4752, L_KB = 6832, L_Y = 6848, L_YB = 8304, L_SIZE = 28656;
constexpr int L_CONST = L_Y, L_KC = L_Y + 10240;
constexpr int TP_0 = 0, TP_W3A = 580, TP_UA = 716, TP_UB = 852, TP_W3B = 988, TP_W5 = 1248, TP_W9 = 1448, TP_W7 = 1648,
              TP_COPY = 1856;
__device__ __forceinline__ int e_off(int ch) { return ch == 0 ? 0 : OFF_ST + (ch - 1) * E_SIZE; }
__device__ __forceinline__ int l_off(int ch) { return 32768 + ch * L_SIZE; }
__device__ __forceinline__ int xg_off(int box) { return box < 4 ? OFF_ST + box * 4096 : 170880 + (box - 4) * 4096; }

__device__ __forceinline__ void ln_load(const __nv_bfloat16* __restrict__ x, const __nv_bfloat16* __restrict__ gate_w,
                                        int row, int lane, uint32_t (&w)[9], uint32_t (&gw)[9]) {
  const uint32_t* xr = reinterpret_cast<const uint32_t*>(x + (size_t)row * D_MOD) + lane;
  const uint32_t* gwp = reinterpret_cast<const uint32_t*>(gate_w) + lane;
#pragma unroll
  for (int j = 0; j < 9; j++) {
    asm volatile("ld.global.nc.u32 %0, [%1];" : "=r"(w[j]) : "l"(xr + j * 32));
    asm volatile("ld.global.nc.u32 %0, [%1];" : "=r"(gw[j]) : "l"(gwp + j * 32));
  }
}
__device__ __forceinline__ void ln_row(int row, int lane, const Scratch& sc, const uint32_t (&w)[9], const uint32_t (&gw)[9]) {
  float s = 0.f, gsum = 0.f;
#pragma unroll
  for (int j = 0; j < 9; j++) {
    uint32_t pr2 = bf2_mul(w[j], gw[j]);
    s += bf_lo(w[j]) + bf_hi(w[j]);
    gsum += bf_lo(pr2) + bf_hi(pr2);
  }
#pragma unroll
  for (int o = 1; o < 32; o <<= 1) { s += __shfl_xor_sync(~0u, s, o); gsum += __shfl_xor_sync(~0u, gsum, o); }
  const float mean = s * (1.0f / 576.0f);
  float vs = 0.f;
#pragma unroll
  for (int j = 0; j < 9; j++) {
    float d0 = bf_lo(w[j]) - mean, d1 = bf_hi(w[j]) - mean;
    vs = fmaf(d0, d0, vs); vs = fmaf(d1, d1, vs);
  }
#pragma unroll
  for (int o = 1; o < 32; o <<= 1) vs += __shfl_xor_sync(~0u, vs, o);
  const float mb = bf_round(mean);
  const float vb = bf_round(vs * (1.0f / 576.0f));
  const float rinv = __frcp_rn(bf_round(__fsqrt_rn(bf_round(vb + 1e-5f))));
  const uint32_t nm2 = pack_bf16(-mb, -mb);
  uint32_t* dst = reinterpret_cast<uint32_t*>(sc.xn + (size_t)row * D_MOD) + lane;
#pragma unroll
  for (int j = 0; j < 9; j++) {
    uint32_t dd = bf2_add(w[j], nm2);
    dst[j * 32] = pack_bf16(bf_lo(dd) * rinv, bf_hi(dd) * rinv);
  }
  if (lane == 0) {
    float gv = bf_round(__fdividef(1.0f, 1.0f + __expf(-bf_round(gsum))));
    float og = bf_round(1.0f - gv);
    sc.gate[row] = make_uint2(pack_bf16(gv, gv), pack_bf16(og, og));
  }
}
__device__ __forceinline__ void mma_bf16(float (&d)[4], uint32_t a0, uint32_t a1, uint32_t a2, uint32_t a3, uint32_t b0, uint32_t b1) {
  asm("mma.sync.aligned.m16n8k16.row.col.f32.bf16.bf16.f32 {%0,%1,%2,%3}, {%4,%5,%6,%7}, {%8,%9}, {%0,%1,%2,%3};"
      : "+f"(d[0]), "+f"(d[1]), "+f"(d[2]), "+f"(d[3]) : "r"(a0), "r"(a1), "r"(a2), "r"(a3), "r"(b0), "r"(b1));
}
__device__ __forceinline__ void mma_tf32(float (&d)[4], float a0, float a1, float a2, float a3, float b0, float b1) {
  asm("mma.sync.aligned.m16n8k8.row.col.f32.tf32.tf32.f32 {%0,%1,%2,%3}, {%4,%5,%6,%7}, {%8,%9}, {%0,%1,%2,%3};"
      : "+f"(d[0]), "+f"(d[1]), "+f"(d[2]), "+f"(d[3])
      : "r"(__float_as_uint(a0)), "r"(__float_as_uint(a1)), "r"(__float_as_uint(a2)), "r"(__float_as_uint(a3)),
        "r"(__float_as_uint(b0)), "r"(__float_as_uint(b1)));
}
__device__ __forceinline__ float2 cexp_l(float al, float th, float l) {
  float mg;
  asm("ex2.approx.ftz.f32 %0, %1;" : "=f"(mg) : "f"(al * l));
  const float tr = th * l;
  return make_float2(mg * __cosf(tr), mg * __sinf(tr));
}
__device__ __forceinline__ float2 cmul(float2 a, float2 b) {
  return make_float2(fmaf(a.x, b.x, -a.y * b.y), fmaf(a.x, b.y, a.y * b.x));
}
__device__ __forceinline__ float2 cmulc(float2 a, float2 b) {
  return make_float2(fmaf(a.x, b.x, -a.y * b.y), fmaf(-a.x, b.y, -a.y * b.x));
}
__device__ __forceinline__ float2 csq(float2 a) { return make_float2(fmaf(a.x, a.x, -a.y * a.y), 2.0f * a.x * a.y); }
#define SM_U32(p) (*reinterpret_cast<uint32_t*>(p))
#define SM_F32(p) (*reinterpret_cast<float*>(p))
#define SM_U16(p) (*reinterpret_cast<unsigned short*>(p))
#define SM_U2(p) (*reinterpret_cast<uint2*>(p))
#define SM_F2(p) (*reinterpret_cast<float2*>(p))
#define SM_U4(p) (*reinterpret_cast<uint4*>(p))
#define SM_F4(p) (*reinterpret_cast<float4*>(p))
template <int OFF, int TAG>
__device__ __forceinline__ uint32_t lds_free(uint32_t base) {
  uint32_t v;
  asm volatile("ld.volatile.shared.u32 %0, [%1+%2]; // %3" : "=r"(v) : "r"(base), "n"(OFF), "n"(TAG));
  return v;
}
template <int K0, int K1, int OFF, int K>
__device__ __forceinline__ void load_tquads_(uint32_t (&q)[K1 - K0][4], uint32_t tp) {
  if constexpr (K >= K0) {
    q[K - K0][0] = lds_free<OFF - 32 * K, 0>(tp);
    q[K - K0][1] = lds_free<OFF - 32 * K - 16, 1>(tp);
    q[K - K0][2] = lds_free<OFF - 32 * K + 16, 2>(tp);
    q[K - K0][3] = lds_free<OFF - 32 * K, 3>(tp);
    load_tquads_<K0, K1, OFF, K - 1>(q, tp);
  }
}
template <int K0, int K1, int OFF>
__device__ __forceinline__ void load_tquads(uint32_t (&q)[K1 - K0][4], uint32_t tp) {
  load_tquads_<K0, K1, OFF, K1 - 1>(q, tp);
}
__device__ __forceinline__ void ldsm4_free(uint32_t (&r)[4], uint32_t addr) {
  asm("ldmatrix.sync.aligned.m8n8.x4.shared.b16 {%0,%1,%2,%3}, [%4];"
      : "=r"(r[0]), "=r"(r[1]), "=r"(r[2]), "=r"(r[3]) : "r"(addr));
}
__device__ __forceinline__ void ldsm4t_free(uint32_t (&r)[4], uint32_t addr) {
  asm("ldmatrix.sync.aligned.m8n8.x4.trans.shared.b16 {%0,%1,%2,%3}, [%4];"
      : "=r"(r[0]), "=r"(r[1]), "=r"(r[2]), "=r"(r[3]) : "r"(addr));
}
__device__ __forceinline__ uint32_t ldg_u16(const __nv_bfloat16* p) {
  unsigned short v;
  asm volatile("ld.global.nc.u16 %0, [%1];" : "=h"(v) : "l"(p));
  return v;
}
__device__ __forceinline__ void ldsm4t(uint32_t (&r)[4], uint32_t addr) {
  asm volatile("ldmatrix.sync.aligned.m8n8.x4.trans.shared.b16 {%0,%1,%2,%3}, [%4];"
               : "=r"(r[0]), "=r"(r[1]), "=r"(r[2]), "=r"(r[3]) : "r"(addr) : "memory");
}
template <int I0, int I1, int K0, int K1, int JMIN, int RB, int TOFF>
__device__ __forceinline__ void band(float (&acc)[I1 - I0][4], uint32_t tp, uint32_t sa, uint32_t za, int lane) {
  uint32_t tq[K1 - K0][4];
  load_tquads<K0, K1, TOFF>(tq, tp);
  constexpr int JL = (I0 - K1 + 1 > JMIN) ? I0 - K1 + 1 : JMIN, JH = I1 - 1 - K0;
  constexpr int JP = (JL >= 0) ? (JL & ~1) : -2;
#pragma unroll
  for (int J2 = JP; J2 <= JH; J2 += 2) {
    uint32_t b[4];
    ldsm4t_free(b, (J2 < 0 && lane < 31) ? za : sa + J2 * 16 * RB);
#pragma unroll
    for (int hf = 0; hf < 2; hf++) {
      const int J = J2 + hf;
#pragma unroll
      for (int k = K0; k < K1; k++) {
        const int I = J + k;
        if (J >= JL && J <= JH && I >= I0 && I < I1)
          mma_bf16(acc[I - I0], tq[k - K0][0], tq[k - K0][1], tq[k - K0][2], tq[k - K0][3], b[2 * hf], b[2 * hf + 1]);
      }
    }
  }
}
template <int I0, int I1>
__device__ __forceinline__ void p8_tiles(uint32_t ea, uint32_t za, char* lb, uint32_t tp, int lane) {
  float acc[I1 - I0][4];
#pragma unroll
  for (int i = 0; i < I1 - I0; i++) { acc[i][0] = acc[i][1] = acc[i][2] = acc[i][3] = 0.f; }
  const uint32_t sa = ea + 32 + lane * 16;
  band<I0, I1, 2, 5, -1, 16, TP_W3A + 160>(acc, tp, sa + E_W3A, za, lane);
  band<I0, I1, 2, 5, 0, 16, TP_UA + 160>(acc, tp, sa + E_UA, za, lane);
  band<I0, I1, 2, 5, 0, 16, TP_UB + 160>(acc, tp, sa + E_UB, za, lane);
  band<I0, I1, 2, 9, 0, 16, TP_W3B + 288>(acc, tp, sa + E_W3B, za, lane);
  band<I0, I1, 4, 9, -1, 16, TP_W5 + 288>(acc, tp, sa + E_W5, za, lane);
  char* a = lb + L_Y + L_YB + 4 * (8 * (lane >> 2) + 2 * (lane & 3));
#pragma unroll
  for (int I = I0; I < I1; I++) {
    SM_F2(a + 4 * (128 * I + 4 * (I >> 1))) = make_float2(acc[I - I0][0], acc[I - I0][1]);
    SM_F2(a + 4 * (128 * I + 4 * (I >> 1)) + 256) = make_float2(acc[I - I0][2], acc[I - I0][3]);
  }
}

struct MlpCtx {
  uint32_t bars;
  uint32_t dA, dB;
  int lane;
};
__device__ __forceinline__ void stage_release(const MlpCtx& c, int slot) {
  if (c.lane == 0) mbar_arrive(c.bars + B_EMPTY + 8 * slot);
}
template <int P>
__device__ __forceinline__ void gelu_part(uint32_t baddr, float (&acc)[48]) {
  asm volatile("" : R8(acc, P * 8)::"memory");
  const uint32_t b0 = bf2_mul(lds32(baddr + P * 32), 0x3f003f00u), b1 = bf2_mul(lds32(baddr + P * 32 + 16), 0x3f003f00u);
  uint32_t r0 = gelu_pack(acc[P * 8 + 0], acc[P * 8 + 1], b0);
  uint32_t r1 = gelu_pack(acc[P * 8 + 2], acc[P * 8 + 3], b0);
  uint32_t r2 = gelu_pack(acc[P * 8 + 4], acc[P * 8 + 5], b1);
  uint32_t r3 = gelu_pack(acc[P * 8 + 6], acc[P * 8 + 7], b1);
  acc[P * 8 + 0] = __uint_as_float(r0);
  acc[P * 8 + 1] = __uint_as_float(r1);
  acc[P * 8 + 2] = __uint_as_float(r2);
  acc[P * 8 + 3] = __uint_as_float(r3);
}
__device__ __forceinline__ void h_push(uint32_t (&h)[144], float (&acc)[48]) {
  asm volatile("" : R8(acc, 0)::"memory");
#pragma unroll
  for (int i = 0; i < 96; i++) h[i] = h[i + 24];
#pragma unroll
  for (int i = 0; i < 24; i++) h[96 + i] = __float_as_uint(acc[(i >> 2) * 8 + (i & 3)]);
}
template <int SB, int I>
__device__ __forceinline__ void p1_mma(const MlpCtx& c, float (&cur)[48]) {
  constexpr int S = SB % 9;
  wgmma_ss_n96<(S | I) != 0, ((S * 16384 + I * 32) >> 4),
               (4096 >> 4 << 16) + (((SB % 6) * STAGE_BYTES + I * 1024) >> 4)>(cur, c.dA, c.dB);
}
template <int SB>
__device__ __forceinline__ void p1_stage(const MlpCtx& c, int j, uint32_t baddr, float (&cur)[48], float (&prev)[48],
                                         uint32_t (&h)[144]) {
  constexpr int S = SB % 9;
  if (SB < 9) mbar_wait(c.bars + B_X + 8 * S, 0);
  mbar_wait(c.bars + B_FULL + 8 * (SB % 6), ((SB / 6) + j) & 1);
  WG_FENCE();
  p1_mma<SB, 0>(c, cur); p1_mma<SB, 1>(c, cur); p1_mma<SB, 2>(c, cur); p1_mma<SB, 3>(c, cur);
  WG_COMMIT();
  if (S >= 1 && S <= 6) gelu_part<(S >= 1 && S <= 6) ? S - 1 : 0>(baddr, prev);
  if (S == 7) h_push(h, prev);
  wg_wait<1>();
  if (SB > 0 || j > 0) stage_release(c, (SB + 5) % 6);
  if (S == 0) fence_regs(prev);
}
template <int SB0>
__device__ __forceinline__ void p1_chunk(const MlpCtx& c, int j, uint32_t baddr, float (&cur)[48], float (&prev)[48],
                                         uint32_t (&h)[144]) {
  p1_stage<SB0 + 0>(c, j, baddr, cur, prev, h); p1_stage<SB0 + 1>(c, j, baddr, cur, prev, h);
  p1_stage<SB0 + 2>(c, j, baddr, cur, prev, h); p1_stage<SB0 + 3>(c, j, baddr, cur, prev, h);
  p1_stage<SB0 + 4>(c, j, baddr, cur, prev, h); p1_stage<SB0 + 5>(c, j, baddr, cur, prev, h);
  p1_stage<SB0 + 6>(c, j, baddr, cur, prev, h); p1_stage<SB0 + 7>(c, j, baddr, cur, prev, h);
  p1_stage<SB0 + 8>(c, j, baddr, cur, prev, h);
}
template <int S, int I>
__device__ __forceinline__ void p2_one(const MlpCtx& c, float (&cur)[32], uint32_t (&h)[144]) {
  constexpr int kk = 6 * S + I;
  wgmma_rs_n64<(S | I) != 0, ((S * STAGE_BYTES + I * 2048) >> 4)>(cur, h[4 * kk], h[4 * kk + 1], h[4 * kk + 2], h[4 * kk + 3], c.dB);
}
template <int S>
__device__ __forceinline__ void p2_mma(const MlpCtx& c, uint32_t parity, float (&cur)[32], uint32_t (&h)[144]) {
  mbar_wait(c.bars + B_FULL + 8 * S, parity);
  WG_FENCE();
  p2_one<S, 0>(c, cur, h); p2_one<S, 1>(c, cur, h); p2_one<S, 2>(c, cur, h);
  p2_one<S, 3>(c, cur, h); p2_one<S, 4>(c, cur, h); p2_one<S, 5>(c, cur, h);
  WG_COMMIT();
}
__device__ __forceinline__ int chunk_of(int pos, int pr, int rank) {
  const int off = (int)(0x03231201ull >> (4 * pos)) & 3;
  const int mine = (0x168 >> pos) & 1;
  return pos == 1 ? 8 : 2 * ((pr + off) & 3) + (mine ? rank : rank ^ 1);
}
__device__ __forceinline__ void bulk_s2peer(uint32_t rdst, uint32_t src, uint32_t bytes, uint32_t rbar) {
  asm volatile("cp.async.bulk.shared::cluster.shared::cta.mbarrier::complete_tx::bytes [%0], [%1], %2, [%3];"
               ::"r"(rdst), "r"(src), "r"(bytes), "r"(rbar) : "memory");
}
__device__ __forceinline__ void bulk_s2g_release(void* gdst, uint32_t src, uint32_t bytes) {
  asm volatile("cp.async.bulk.global.shared::cta.bulk_group [%0], [%1], %2;\n"
               "cp.async.bulk.commit_group;\ncp.async.bulk.wait_group 0;\nfence.acq_rel.gpu;"
               ::"l"(gdst), "r"(src), "r"(bytes) : "memory");
}
struct Args {
  const __nv_bfloat16 *u, *Are, *Aim, *Bre, *Bim, *Cre, *Cim, *logdt, *Dskip, *gate_w, *w1, *w2, *b1, *b2;
  __nv_bfloat16* out;
};

struct Maps { const CUtensorMap *x, *w1, *xn; };
__device__ __forceinline__ void load_params(uint32_t (&v)[8], const Args& ar, int d, int n) {
  const int idx = d * N_ST + n;
  v[0] = ldg_u16(ar.Are + idx); v[1] = ldg_u16(ar.Aim + idx); v[2] = ldg_u16(ar.Bre + idx); v[3] = ldg_u16(ar.Bim + idx);
  v[4] = ldg_u16(ar.Cre + idx); v[5] = ldg_u16(ar.Cim + idx); v[6] = ldg_u16(ar.logdt + d); v[7] = ldg_u16(ar.Dskip + d);
}
__device__ __forceinline__ uint4 pack_params(uint32_t (&v)[8]) {
  asm volatile("" : "+r"(v[0]), "+r"(v[1]), "+r"(v[2]), "+r"(v[3]), "+r"(v[4]), "+r"(v[5]), "+r"(v[6]), "+r"(v[7])::"memory");
  return make_uint4(v[0] | (v[1] << 16), v[2] | (v[3] << 16), v[4] | (v[5] << 16), v[6] | (v[7] << 16));
}
__device__ __noinline__ uint4 ssm_pass(const Maps tm, char* sm, const int d0, const int pass, const uint4 pv
) {
  const Args& ar = *reinterpret_cast<const Args*>(sm + OFF_ARGS);
  const Scratch& sc = *reinterpret_cast<const Scratch*>(sm + OFF_ARGS + 128);
  const uint32_t sb = smem_u32(sm), bars = sb + OFF_BAR;
  const int tid = threadIdx.x, lane = tid & 31;
  const int warp = __shfl_sync(0xffffffffu, tid >> 5, 0);
  const int bid = blockIdx.x, m = bid >> 3, f = bid & 7;
  const int g = lane >> 2, cc = lane & 3;
  const int ch = warp >> 2, n = tid & 127;
  char* eb = sm + e_off(ch);
  char* lb = sm + l_off(ch);
#define CH_SYNC() asm volatile("bar.sync %0, 128;" ::"r"(ch + 1) : "memory")
  const bool lead = warp < 8;
  {
    const float are = bf_lo(pv.x), aim = bf_hi(pv.x), bre = bf_lo(pv.y), bim = bf_hi(pv.y);
    const float cre = bf_lo(pv.z), cim = bf_hi(pv.z), ldt = bf_lo(pv.w), dsk = bf_hi(pv.w);
    const float dt = bf_round(expf(ldt));
    const float al = (dt * are) * 1.4426950408889634f, th = dt * aim;
    constexpr float TF32_UNBIAS = 1.0f + 0.7f / 1024.0f;
    const float2 c0 = cmul(make_float2(cre * TF32_UNBIAS, cim * TF32_UNBIAS), make_float2(dt * bre, dt * bim));
    const float2 e64 = cexp_l(al, th, 64.f), e128 = csq(e64), e256 = cexp_l(al, th, 256.f), e512 = csq(e256);
    const float2 k128 = cmul(c0, e128), k256 = cmul(c0, e256), k384 = cmul(k256, e128);
    const float2 k512 = cmul(c0, e512), k516 = cmul(k512, cexp_l(al, th, 4.f));
    const float2 e1024 = cexp_l(al, th, 1024.f), k1024 = cmul(c0, e1024);
    float k2048 = fmaf(k1024.x, e1024.x, -k1024.y * e1024.y) * (1.0f / TF32_UNBIAS);
    char* ca = lb + L_CONST + n * 80;
    SM_F4(ca) = make_float4(al, th, e64.x, e64.y);
    SM_F4(ca + 16) = make_float4(c0.x, c0.y, k128.x, k128.y);
    SM_F4(ca + 32) = make_float4(k256.x, k256.y, k384.x, k384.y);
    SM_F4(ca + 48) = make_float4(k512.x, k512.y, k516.x, k516.y);
    SM_F2(ca + 64) = k1024;
#pragma unroll
    for (int o = 16; o > 0; o >>= 1) k2048 += __shfl_xor_sync(~0u, k2048, o);
    if (lane == 0) SM_F32(lb + L_KC + (warp & 3) * 2576 + 2560) = k2048;
    if (n == 0) SM_F32(lb + L_KB + 8) = dsk;
    __syncwarp();
    DBG_S(0);
    float kd[5][4];
#pragma unroll
    for (int t = 0; t < 5; t++) { kd[t][0] = kd[t][1] = kd[t][2] = kd[t][3] = 0.f; }
    const float l1 = (float)g, l128 = (float)(128 * g);
    const char* cr = lb + L_CONST + ((warp & 3) * 32 + cc) * 80;
    const int o2 = 32 + (g >> 2) * 8, o3 = 48 + (g & 1) * 8, s2 = ((g & 3) << 2) | cc, s3 = ((g >> 1) << 2) | cc;
#pragma unroll 2
    for (int st = 0; st < 8; st++, cr += 320) {
      const float4 q0 = *(const float4*)cr, q1 = *(const float4*)(cr + 16);
      const float2 q2 = *(const float2*)(cr + o2), q3 = *(const float2*)(cr + o3), q4 = *(const float2*)(cr + 64);
      const float2 p1 = cexp_l(q0.x, q0.y, l1), p128 = cexp_l(q0.x, q0.y, l128);
      const float2 p2 = csq(p1), p8 = csq(csq(p2));
      const float2 a1 = cmul(p8, make_float2(q0.z, q0.w));
      float2 x = cmulc(make_float2(q1.x, q1.y), p1);
      mma_tf32(kd[0], p8.x, a1.x, p8.y, a1.y, x.x, x.y);
      x = cmulc(make_float2(q1.z, q1.w), p1);
      mma_tf32(kd[1], p8.x, a1.x, p8.y, a1.y, x.x, x.y);
      x = cmulc(q2, make_float2(__shfl_sync(~0u, p2.x, s2), __shfl_sync(~0u, p2.y, s2)));
      mma_tf32(kd[2], p8.x, a1.x, p8.y, a1.y, x.x, x.y);
      x = cmulc(q3, make_float2(__shfl_sync(~0u, p128.x, s3), __shfl_sync(~0u, p128.y, s3)));
      mma_tf32(kd[3], p8.x, a1.x, p8.y, a1.y, x.x, x.y);
      x = cmulc(q4, p128);
      mma_tf32(kd[4], p8.x, a1.x, p8.y, a1.y, x.x, x.y);
    }
    char* kc = lb + L_KC + (warp & 3) * 2576;
#pragma unroll
    for (int e = 0; e < 2; e++) {
      const int row = g + e * 8;
      SM_F2(kc + 4 * (8 * row + 2 * cc)) = make_float2(kd[0][2 * e], kd[0][2 * e + 1]);
      SM_F2(kc + 4 * (128 + 8 * row + 2 * cc)) = make_float2(kd[1][2 * e], kd[1][2 * e + 1]);
      SM_F2(kc + 4 * (256 + 64 * (cc >> 1) + 4 * row + 2 * (cc & 1))) = make_float2(kd[2][2 * e], kd[2][2 * e + 1]);
      SM_F2(kc + 4 * (384 + 32 * cc + 2 * row)) = make_float2(kd[3][2 * e], kd[3][2 * e + 1]);
      SM_F32(kc + 4 * (512 + 32 * cc + row)) = kd[4][2 * e];
      SM_F32(kc + 4 * (528 + 32 * cc + row)) = kd[4][2 * e + 1];
    }
  }
  DBG_S(1);
  CH_SYNC();
  {
    const char* kc = lb + L_KC;
    auto kq = [&](int idx) {
      const char* q = kc + 4 * idx;
      return (*(const float*)q + *(const float*)(q + 2576)) + (*(const float*)(q + 5152) + *(const float*)(q + 7728));
    };
#pragma unroll
    for (int it = 0; it < 5; it++) {
      const int idx = n + 128 * it;
      float t = kq(idx);
      if ((it == 1 || it == 2) && n == 127) t -= kq(idx + 1);
      if (it == 4 && n == 0) { SM_F2(lb + L_KB) = make_float2(t, kq(640)); t = 0.f; }
      int off;
      if (it < 2) off = TP_0 + 2 * (272 - idx);
      else if (it == 2) {
        const int sel = n & 3, mu = 32 + (n >> 2);
        off = sel == 2 ? TP_W3B + 2 * (144 - mu) : (sel == 0 ? TP_W3A : sel == 1 ? TP_UA : TP_UB) + 2 * (80 - mu);
      } else if (it == 3) off = ((n & 1) ? TP_W3B : TP_W5) + 2 * (80 - (n >> 1));
      else off = ((n & 1) ? TP_W7 : TP_W9) + 2 * (80 - (n >> 1));
      const unsigned short hv = pack_bf16(t, 0.f);
      SM_U16(eb + E_TAP + off) = hv;
      SM_U16(eb + E_TAP + TP_COPY + off + 2) = hv;
    }
  }
  DBG_S(2);
  if (!lead && bid < 128) {
    uint32_t lw[9], lx[9], lg[9];
    const int row = bid * 16 + (warp - 8) * 2;
    ln_load(ar.u, ar.gate_w, row, lane, lw, lg);
    ln_load(ar.u, ar.gate_w, row + 1, lane, lx, lg);
    ln_row(row, lane, sc, lw, lg);
    ln_row(row + 1, lane, sc, lx, lg);
    asm volatile("bar.sync 5, 256;" ::: "memory");
  }
  if (lead) {
    mbar_wait(bars + B_U, pass & 1);
    if (pass > 0) mbar_wait(bars + B_COMB, (pass - 1) & 1);
    const uint32_t src = sb + xg_off(warp) + lane * 16;
    const int mych = g - (d0 & 4);
    char* dst = sm + l_off(mych) + (warp + 1) * 528 + cc * 4;
#pragma unroll
    for (int i = 0; i < 8; i++) {
      uint32_t r[4];
      ldsm4t(r, src + i * 512);
      if (mych >= 0 && mych < 4) {
#pragma unroll
        for (int k = 0; k < 4; k++) SM_U32(dst + i * 64 + k * 16) = r[k];
      }
    }
    __syncwarp();
    if (lane == 0) mbar_arrive(bars + B_U0);
    if (bid < 128 && tid == 0) {
      asm volatile("cp.async.bulk.prefetch.L2.global [%0], %1;" ::"l"(ar.w1 + (size_t)bid * 20736), "r"(41472) : "memory");
      asm volatile("cp.async.bulk.prefetch.L2.global [%0], %1;" ::"l"(ar.w2 + (size_t)bid * 20736), "r"(41472) : "memory");
    }
  }
  DBG_S(3);
  mbar_wait(bars + B_U0, pass & 1);
  DBG_S(4);
#pragma unroll 1
  for (int i = n - 1; i < 224; i += 128) {
    const char* ur = lb + ((i >> 5) + 1) * 528 + (i & 31) * 16;
    const uint4 w0 = *(const uint4*)(ur - ((i & 31) ? 16 : 32) + (i < 0 ? 16 : 0)), w1 = *(const uint4*)ur,
                w2 = *(const uint4*)(ur + ((i & 31) == 31 ? 32 : 16));
    const uint32_t wv[12] = {w0.x, w0.y, w0.z, w0.w, w1.x, w1.y, w1.z, w1.w, w2.x, w2.y, w2.z, w2.w};
    char* o = eb + 32 + 16 * i;
    SM_U4(o + E_UA) = make_uint4(wv[3], wv[4], wv[5], wv[6]);
    SM_U4(o + E_UB) = make_uint4(wv[1], wv[2], wv[3], wv[4]);
    float v[22], wa[16];
#pragma unroll
    for (int k = 1; k < 11; k++) { v[2 * k] = bf_lo(wv[k]); v[2 * k + 1] = bf_hi(wv[k]); }
#pragma unroll
    for (int k = 4; k < 16; k++) wa[k] = (v[k - 1] + v[k]) + v[k + 1];
    SM_U4(o + E_W3A) = make_uint4(pack_bf16(wa[8], wa[9]), pack_bf16(wa[10], wa[11]), pack_bf16(wa[12], wa[13]), pack_bf16(wa[14], wa[15]));
    SM_U4(o + E_W3B) = make_uint4(pack_bf16(wa[4], wa[5]), pack_bf16(wa[6], wa[7]), pack_bf16(wa[8], wa[9]), pack_bf16(wa[10], wa[11]));
    if (i < 192) {
#pragma unroll
      for (int k = 8; k < 16; k++) wa[k] += v[k - 2] + v[k + 2];
      SM_U4(o + E_W5) = make_uint4(pack_bf16(wa[8], wa[9]), pack_bf16(wa[10], wa[11]), pack_bf16(wa[12], wa[13]), pack_bf16(wa[14], wa[15]));
      if (i < 128) {
#pragma unroll
        for (int k = 8; k < 16; k++) wa[k] += v[k - 3] + v[k + 3];
        SM_U4(lb + L_W7 + 32 + 16 * i) =
            make_uint4(pack_bf16(wa[8], wa[9]), pack_bf16(wa[10], wa[11]), pack_bf16(wa[12], wa[13]), pack_bf16(wa[14], wa[15]));
#pragma unroll
        for (int k = 8; k < 16; k++) wa[k] += v[k - 4] + v[k + 4];
        SM_U4(o + E_W9) = make_uint4(pack_bf16(wa[8], wa[9]), pack_bf16(wa[10], wa[11]), pack_bf16(wa[12], wa[13]), pack_bf16(wa[14], wa[15]));
      }
    }
  }
  if (bid < 128 && tid == 480) {
    asm volatile("fence.acq_rel.gpu;" ::: "memory");
    atomicAdd(&sc.flags[256 + m], 1u);
  }
  __syncwarp();
  CH_SYNC();
  DBG_S(5);
  {
    const int role = (warp + ch) & 3;
    uint32_t ea = smem_u32(eb), za = smem_u32(lb);
    asm volatile("" : "+r"(ea), "+r"(za)::"memory");
    const uint32_t tp = ea + E_TAP + ((g & 1) ? TP_COPY + 2 : 0) - 2 * (g - 2 * cc);
    if (role < 2) {
      uint32_t ta[17][4];
      load_tquads<0, 17, TP_0 + 544>(ta, tp);
      float acc[8][4];
#pragma unroll
      for (int i = 0; i < 8; i++) { acc[i][0] = acc[i][1] = acc[i][2] = acc[i][3] = 0.f; }
      const uint32_t bpos = za + ((lane & 7) + 1) * 528 + role * 256 + (lane >> 3) * 16;
      const uint32_t bmid = role ? bpos : bpos - 16;
#pragma unroll
      for (int j2 = -16; j2 < 8; j2 += 2) {
        uint32_t b[4];
        ldsm4_free(b, (j2 < -8 ? bpos - 16 : j2 < 0 ? bmid : bpos) + 32 * j2);
#pragma unroll
        for (int hf = 0; hf < 2; hf++) {
#pragma unroll
          for (int i = 0; i < 8; i++) {
            const int k = i - j2 - hf;
            if (k >= 0 && k <= 16) mma_bf16(acc[i], ta[k][0], ta[k][1], ta[k][2], ta[k][3], b[2 * hf], b[2 * hf + 1]);
          }
        }
      }
      char* ya = lb + L_Y + 4 * (520 * cc + 128 * role + g);
#pragma unroll
      for (int i = 0; i < 8; i++) {
        SM_F32(ya + 64 * i) = acc[i][0]; SM_F32(ya + 64 * i + 1040) = acc[i][1];
        SM_F32(ya + 64 * i + 32) = acc[i][2]; SM_F32(ya + 64 * i + 1072) = acc[i][3];
      }
    } else if (role == 2) {
      p8_tiles<1, 11>(ea, za, lb, tp, lane);
    } else {
      p8_tiles<11, 16>(ea, za, lb, tp, lane);
      float acc[2][5][4];
#pragma unroll
      for (int i = 0; i < 10; i++) { acc[i / 5][i % 5][0] = acc[i / 5][i % 5][1] = acc[i / 5][i % 5][2] = acc[i / 5][i % 5][3] = 0.f; }
#pragma unroll
      for (int sg = 0; sg < 2; sg++) {
        uint32_t tq[5][4];
        if (sg == 0) load_tquads<4, 9, TP_W9 + 288>(tq, tp); else load_tquads<4, 9, TP_W7 + 288>(tq, tp);
        const uint32_t sa = (sg == 0 ? ea + E_W9 : za + L_W7 - 16) + 32 + (lane & 15) * 32 + (lane >> 4) * 16;
#pragma unroll
        for (int J = -1 + sg; J < 4; J++) {
          uint32_t b[4];
          ldsm4t_free(b, (J < 0 && (lane & 15) < 15) ? za : sa + J * 512);
#pragma unroll
          for (int k = 4; k < 9; k++) {
            const int I = J + k;
            if (I < 8) {
              mma_bf16(acc[0][I - 3], tq[k - 4][0], tq[k - 4][1], tq[k - 4][2], tq[k - 4][3], b[0], b[1]);
              mma_bf16(acc[1][I - 3], tq[k - 4][0], tq[k - 4][1], tq[k - 4][2], tq[k - 4][3], b[2], b[3]);
            }
          }
        }
      }
      char* a = lb + L_Y + 2 * L_YB + 4 * (16 * g + 2 * cc);
#pragma unroll
      for (int hh = 0; hh < 2; hh++) {
#pragma unroll
        for (int I = 3; I < 8; I++) {
          SM_F2(a + 32 * hh + 1040 * (I - 3)) = make_float2(acc[hh][I - 3][0], acc[hh][I - 3][1]);
          SM_F2(a + 32 * hh + 1040 * (I - 3) + 512) = make_float2(acc[hh][I - 3][2], acc[hh][I - 3][3]);
        }
      }
    }
  }
  __syncwarp();
  if (lane == 0) {
    mbar_arrive(bars + B_CONV);
    if (!lead) {
      const int iw = warp - 8;
      mbar_wait(bars + B_CONV, pass & 1);
      HFENCE();
      if (bid >= 128) {
        if (pass < 3) {
          mbar_expect_tx(bars + B_U, 4096);
          tma2d(sb + xg_off(iw), tm.x, (d0 + 4) & ~7, iw * 256, bars + B_U);
        }
      } else if (iw < 6) {
        mbar_expect_tx(bars + B_FULL + 8 * iw, STAGE_BYTES);
        tma3d(sb + OFF_ST + iw * STAGE_BYTES, tm.w1, 0, iw * 64, f * 18, bars + B_FULL + 8 * iw);
      } else {
        wait_flag(&sc.flags[256 + m], 8);
        mbar_expect_tx(bars + B_X + 8 * (iw - 6), 16384);
        tma2d(sb + (iw - 6) * 16384, tm.xn, (iw - 6) * 64, m * 128, bars + B_X + 8 * (iw - 6));
      }
    }
  }
  __syncwarp();
  CH_SYNC();
  DBG_S(6);
  uint32_t pnext[8];
#pragma unroll
  for (int i = 0; i < 8; i++) pnext[i] = 0;
  if (bid >= 128 && pass < 3) load_params(pnext, ar, d0 + 4 + ch, n);
  {
    const float4 kb = SM_F4(lb + L_KB);
    const uint32_t dk = pack_bf16(kb.z, kb.z);
#pragma unroll
    for (int k = 0; k < 4; k++) {
      const int t0 = n * 4 + 512 * k;
      char* ya = lb + L_Y + 4 * (t0 + 4 * (t0 >> 8));
      float4 y = SM_F4(ya);
      if (k > 0 || t0 >= 128) { const float4 b = SM_F4(ya + L_YB); y.x += b.x; y.y += b.y; y.z += b.z; y.w += b.w; }
      if (k > 1 || (k == 1 && t0 >= 768)) {
        const float4 b = SM_F4(ya + 2 * L_YB - 3120);
        y.x += b.x; y.y += b.y; y.z += b.z; y.w += b.w;
        if (k > 1 || t0 >= 1020) {
          const char* wp = lb + L_W7 + 32 + 2 * (t0 - 1026);
          const uint32_t wl = *(const uint32_t*)wp, wm = *(const uint32_t*)(wp + 4), wh = *(const uint32_t*)(wp + 8);
          y.x = fmaf(kb.x, bf_hi(wl), y.x); y.y = fmaf(kb.x, bf_lo(wm), y.y);
          y.z = fmaf(kb.x, bf_hi(wm), y.z); y.w = fmaf(kb.x, bf_lo(wh), y.w);
          if (k == 3 && n == 127) {
            const uint2 u03 = SM_U2(lb + 528);
            float pre = bf_lo(u03.x);
            y.x = fmaf(kb.y, pre, y.x); pre += bf_hi(u03.x);
            y.y = fmaf(kb.y, pre, y.y); pre += bf_lo(u03.y);
            y.z = fmaf(kb.y, pre, y.z); pre += bf_hi(u03.y);
            y.w = fmaf(kb.y, pre, y.w);
          }
        }
      }
      const uint2 uu = SM_U2(lb + ((t0 >> 8) + 1) * 528 + (t0 & 255) * 2);
      uint2 o;
      o.x = bf2_add(pack_bf16(y.x, y.y), bf2_mul(uu.x, dk));
      o.y = bf2_add(pack_bf16(y.z, y.w), bf2_mul(uu.y, dk));
      *reinterpret_cast<uint2*>(sc.aT + (size_t)(d0 + ch) * L_SEQ + t0) = o;
    }
  }
  __syncwarp();
  if (lane == 0) mbar_arrive(bars + B_COMB);
  CH_SYNC();
  DBG_S(7);
  return pack_params(pnext);
}

__global__ void __cluster_dims__(2, 1, 1) __launch_bounds__(512, 1)
fused_kernel(const __grid_constant__ CUtensorMap tm_x, const __grid_constant__ CUtensorMap tm_w1,
             const __grid_constant__ CUtensorMap tm_w2, const __grid_constant__ CUtensorMap tm_aT,
             const __grid_constant__ CUtensorMap tm_xn, const __grid_constant__ CUtensorMap tm_out,
             const __grid_constant__ CUtensorMap tm_a8,
             const __grid_constant__ Args ar, const __grid_constant__ Scratch sc) {
  extern __shared__ __align__(1024) char smem_raw[];
  DBG_G(28);
  const uint32_t sb = (smem_u32(smem_raw) + 1023) & ~1023u;
  char* sm = smem_raw + (sb - smem_u32(smem_raw));
  const uint32_t bars = sb + OFF_BAR;
  const int tid = threadIdx.x, lane = tid & 31;
  const int warp = __shfl_sync(0xffffffffu, tid >> 5, 0), wg = warp >> 2;
  const int bid = blockIdx.x;
  const int m = bid >> 3, f = bid & 7, rank = f & 1, pr = f >> 1;

  const int dbase = bid < 128 ? bid * 4 : 512 + (bid - 128) * 16;
  uint32_t praw[8];
  load_params(praw, ar, dbase + wg, tid & 127);

  if (lane == 0) {
    if (warp == 8) {
#pragma unroll
      for (int i = 0; i < B_EMPTY / 8; i++) mbar_init(bars + i * 8, 1);
      asm volatile("fence.mbarrier_init.release.cluster;" ::: "memory");
#pragma unroll
      for (int i = 0; i < 4; i++) mbar_expect_tx(bars + B_RB + 8 * i, 16384);
    } else if (warp == 9) {
#pragma unroll
      for (int i = B_EMPTY / 8; i < NBARS; i++) mbar_init(bars + i * 8, 8);
      mbar_init(bars + B_CONV, 16);
      mbar_init(bars + B_COMB, 16);
      asm volatile("fence.mbarrier_init.release.cluster;" ::: "memory");
    } else if (warp == 10) {
      asm volatile("prefetch.tensormap [%0];" ::"l"(&tm_x) : "memory");
    } else if (warp == 11) {
      *reinterpret_cast<Args*>(sm + OFF_ARGS) = ar;
      *reinterpret_cast<Scratch*>(sm + OFF_ARGS + 128) = sc;
    }
  }
  __syncthreads();
  asm volatile("barrier.cluster.arrive.relaxed.aligned;" ::: "memory");

  {
    Maps tm;
    tm.x = &tm_x; tm.w1 = &tm_w1; tm.xn = &tm_xn;
    const int npass = bid < 128 ? 1 : 4;
    if (lane == 0 && (warp & 1) == 0) {
      mbar_expect_tx(bars + B_U, 4096);
      tma2d(sb + xg_off(warp >> 1), &tm_x, dbase & ~7, (warp >> 1) * 256, bars + B_U);
    }
    {
      char* eb = sm + e_off(wg);
      const int n = tid & 127;
      const uint4 z = make_uint4(0, 0, 0, 0);
      SM_U4(eb + E_TAP + n * 16) = z;
      if (n < 104) SM_U4(eb + E_TAP + 2048 + n * 16) = z;
      else if (n == 104) SM_U4(eb + E_W9) = z;
      if (n < 33) SM_U4(sm + l_off(wg) + n * 16) = z;
    }
    uint4 pv = pack_params(praw);
#pragma unroll 1
    for (int pass = 0; pass < npass; pass++)
      pv = ssm_pass(tm, sm, dbase + pass * 4, pass, pv
      );
  }
  __syncthreads();
  if (bid >= 128) {
    if (tid == 0) {
      asm volatile("fence.acq_rel.gpu;" ::: "memory");
      atomicAdd(&sc.flags[304], 1u);
    }
    __syncwarp();
    asm volatile("barrier.cluster.wait.acquire.aligned;" ::: "memory");
    return;
  }

  const uint32_t rdelta = mapa(sb, rank ^ 1) - sb;
  if (wg >= 2) {
    asm volatile("setmaxnreg.dec.sync.aligned.u32 24;");
    asm volatile("barrier.cluster.wait.acquire.aligned;" ::: "memory");
    const int pw = warp - 8;
    if (lane == 0) {
      if (pw < 2) {
        int slot = pw, par = 0;
#pragma unroll 1
        for (int it = 6 + pw; it < 54; it += 2) {
          const int ch = it / 9, s = it - ch * 9;
          const uint32_t fb = bars + B_FULL + 8 * slot;
          mbar_wait(bars + B_EMPTY + 8 * slot, par);
          mbar_expect_tx(fb, STAGE_BYTES);
          tma3d(sb + OFF_ST + slot * STAGE_BYTES, &tm_w1, 0, s * 64, f * 18 + ch * 3, fb);
          slot += 2;
          if (slot >= 6) { slot -= 6; par ^= 1; }
        }
#pragma unroll 1
        for (int pos = 0; pos < 9; pos++) {
          const int chunk = chunk_of(pos, pr, rank);
#pragma unroll 1
          for (slot = pw; slot < 6; slot += 2) {
            const uint32_t fb = bars + B_FULL + 8 * slot;
            mbar_wait(bars + B_EMPTY + 8 * slot, par);
            mbar_expect_tx(fb, STAGE_BYTES);
            tma2d(sb + OFF_ST + slot * STAGE_BYTES, &tm_w2, chunk * 64, f * 576 + slot * 96, fb);
          }
          par ^= 1;
        }
        if (pw == 0) {
          wait_flag(&sc.flags[288 + f * 2], 16);
          mbar_wait(bars + B_EMPTY, par);
          mbar_wait(bars + B_EMPTY + 8, par);
          mbar_expect_tx(bars + B_FULL, 16384);
          tma2d(sb + OFF_ST, &tm_aT, m * 128, f * 64, bars + B_FULL);
          tma2d(sb + OFF_ST + 8192, &tm_aT, m * 128 + 64, f * 64, bars + B_FULL);
          if (atomicAdd(&sc.flags[289 + f * 2], 1u) == 15) { sc.flags[288 + f * 2] = 0; sc.flags[289 + f * 2] = 0; }
        }
      } else if (pw == 2) {
        mbar_wait(bars + B_P1R, 0);
#pragma unroll 1
        for (int k = 0; k < 4; k++) {
          mbar_wait(bars + B_TS + 8 * k, 0);
          HFENCE();
          bulk_s2peer(sb + k * 16384 + rdelta, sb + OFF_STG + k * 16384, 16384, bars + B_RB + 8 * k + rdelta);
        }
#pragma unroll 1
        for (int k = 0; k < 4; k++) mbar_wait(bars + B_RB + 8 * k, 0);
        mbar_arrive_remote(bars + B_FIN + rdelta);
        mbar_wait(bars + B_FIN, 0);
      } else if (pw == 3) {
        mbar_wait(bars + B_TS8, 0);
        HFENCE();
        bulk_s2g_release(sc.slots8 + (size_t)(m * 8 + f) * 4096, sb + OFF_C8, 16384);
#pragma unroll 1
        for (int i = 0; i < 8; i++) atomicAdd(&sc.flags[m * 16 + 8 + i], 1u);
#pragma unroll 1
        for (int k = 0; k < 3; k++) {
          const int chunk = 2 * ((pr + k + 1) & 3) + rank;
          mbar_wait(bars + B_TR + 8 * k, 0);
          HFENCE();
          bulk_s2g_release(sc.slots + (size_t)((m * 8 + chunk) * 3 + k) * 4096, sb + k * 16384, 16384);
          atomicAdd(&sc.flags[320 + (m * 8 + chunk) * 4 + k], 1u);
          DBG_H(16 + k);
          if (k == 0) {
            mbar_expect_tx(bars + B_OWN, 65536);
            wait_flag(&sc.flags[m * 16 + 8 + f], 8);
            sc.flags[m * 16 + 8 + f] = 0;
#pragma unroll 1
            for (int i = 0; i < 8; i++)
              bulk_g2s(sb + OFF_C8 + i * 2048, sc.slots8 + (size_t)(m * 8 + i) * 4096 + f * 512, 2048, bars + B_OWN);
          }
#pragma unroll 1
          for (int j = k - 1; j >= 0 && j <= k; j += (k == 2 ? 1 : 2)) {
            unsigned int* fl = &sc.flags[320 + (m * 8 + f) * 4 + j];
            wait_flag(fl, 1);
            *fl = 0;
            bulk_g2s(sb + j * 16384, sc.slots + (size_t)((m * 8 + f) * 3 + j) * 4096, 16384, bars + B_OWN);
          }
        }
        if (f == 0) sc.flags[256 + m] = 0;
        DBG_H(19);
      } else if (pw == 4) {
        asm volatile("fence.acq_rel.gpu;" ::: "memory");
        atomicAdd(&sc.flags[288 + (bid >> 4) * 2], 1u);
        mbar_wait(bars + B_TR + 8, 0);
        wait_flag(&sc.flags[304], 4);
        mbar_expect_tx(bars + B_A8, 2048);
        tma2d(sb + OFF_A8, &tm_a8, m * 128, 512 + f * 8, bars + B_A8);
        if (atomicAdd(&sc.flags[305], 1u) == 127) { sc.flags[304] = 0; sc.flags[305] = 0; }
      } else {
        HFENCE();
#pragma unroll 1
        for (int kb = pw - 3; kb < 9; kb += 3) {
          mbar_expect_tx(bars + B_X + 8 * kb, kb == 8 ? 16384 + 2304 : 16384);
          tma2d(sb + kb * 16384, &tm_xn, kb * 64, m * 128, bars + B_X + 8 * kb);
          if (kb == 8) {
            bulk_g2s(sb + OFF_B1, ar.b1 + f * 576, 1152, bars + B_X + 64);
            bulk_g2s(sb + OFF_B2, ar.b2, 1152, bars + B_X + 64);
          }
        }
      }
    }
  } else {
    asm volatile("setmaxnreg.inc.sync.aligned.u32 232;");
    const int wi = warp & 3;
    DBG_T(0);
    MlpCtx c;
    c.bars = bars; c.lane = lane;
    c.dA = (((sb + wg * 8192) & 0x3FFFF) >> 4) | (1u << 16);
    c.dB = ((sb + OFF_ST) & 0x3FFFF) >> 4;

    uint32_t h[144];
    float acc2a[32], acc2b[32];
    {
      float accA[48], accB[48];
#pragma unroll
      for (int i = 0; i < 48; i++) { accA[i] = 0.f; accB[i] = 0.f; }
#pragma unroll
      for (int i = 0; i < 144; i++) h[i] = 0;
      uint32_t baddr = sb + OFF_B1 + (lane & 3) * 4 - 192;
#pragma unroll 1
      for (int j = 0; j < 3; j++) {
        DBG_T(11 + 2 * j);
        p1_chunk<0>(c, j, baddr, accA, accB, h);
        baddr += 192;
        DBG_T(10 + 2 * j);
        p1_chunk<9>(c, j, baddr, accB, accA, h);
        baddr += 192;
      }
      DBG_T(2);
      p2_mma<0>(c, 1, acc2a, h);
      wg_wait<1>();
      stage_release(c, 5);
      fence_regs(accB);
      asm volatile("barrier.cluster.wait.acquire.aligned;" ::: "memory");
      if (lane == 0) { mbar_arrive(bars + B_P1L); mbar_arrive_remote(bars + B_P1R + rdelta); }
      p2_mma<1>(c, 1, acc2a, h);
      gelu_part<0>(baddr, accB); gelu_part<1>(baddr, accB);
      wg_wait<1>(); stage_release(c, 0);
      p2_mma<2>(c, 1, acc2a, h);
      gelu_part<2>(baddr, accB); gelu_part<3>(baddr, accB);
      wg_wait<1>(); stage_release(c, 1);
      p2_mma<3>(c, 1, acc2a, h);
      gelu_part<4>(baddr, accB);
      wg_wait<1>(); stage_release(c, 2);
      p2_mma<4>(c, 1, acc2a, h);
      gelu_part<5>(baddr, accB);
#pragma unroll
      for (int i = 0; i < 24; i++) h[120 + i] = __float_as_uint(accB[(i >> 2) * 8 + (i & 3)]);
      wg_wait<1>(); stage_release(c, 3);
      p2_mma<5>(c, 1, acc2a, h);
      wg_wait<1>(); stage_release(c, 4);
    }
    const uint32_t lbuf = sb + warp * 2048 + lane * 16;
    mbar_wait(bars + B_P1L, 0);
#pragma unroll 1
    for (int pos = 0; pos < 8; pos++) {
      const bool recv = (0x68 >> pos) & 1;
      const int k = recv ? (pos - 2) >> 1 : (pos + 1) >> 1;
      const int ks = k > 3 ? 3 : k;
      const uint32_t addr = lbuf + ks * 16384 + (recv ? 0 : OFF_STG);
      const uint32_t sig = bars + (recv ? B_TR + 8 * k : pos == 1 ? B_TS8 : B_TS + 8 * ks);
      if (recv) mbar_wait(bars + B_RB + k * 8, 0);
      wg_wait<0>(); stage_release(c, 5);
      fence_regs(acc2a);
      DBG_T(20 + pos);
      if (recv) {
#pragma unroll
        for (int i = 0; i < 4; i++) {
          const float4 r = lds128f(addr + i * 512);
          const uint32_t w0 = __float_as_uint(r.x), w1 = __float_as_uint(r.y), w2 = __float_as_uint(r.z), w3 = __float_as_uint(r.w);
          acc2a[8 * i + 0] += bf_lo(w0); acc2a[8 * i + 1] += bf_hi(w0); acc2a[8 * i + 2] += bf_lo(w1); acc2a[8 * i + 3] += bf_hi(w1);
          acc2a[8 * i + 4] += bf_lo(w2); acc2a[8 * i + 5] += bf_hi(w2); acc2a[8 * i + 6] += bf_lo(w3); acc2a[8 * i + 7] += bf_hi(w3);
        }
      }
      if (pos == 1) {
        const uint32_t a8 = sb + OFF_C8 + warp * 256 + lane * 8;
#pragma unroll
        for (int q = 0; q < 8; q++)
          asm volatile("st.shared.v2.u32 [%0], {%1,%2};" ::"r"(a8 + q * 2048), "r"(pack_bf16(acc2a[4 * q], acc2a[4 * q + 1])),
                       "r"(pack_bf16(acc2a[4 * q + 2], acc2a[4 * q + 3])) : "memory");
      } else {
#pragma unroll
        for (int i = 0; i < 4; i++)
          sts128(addr + i * 512, pack_bf16(acc2a[8 * i], acc2a[8 * i + 1]), pack_bf16(acc2a[8 * i + 2], acc2a[8 * i + 3]),
                 pack_bf16(acc2a[8 * i + 4], acc2a[8 * i + 5]), pack_bf16(acc2a[8 * i + 6], acc2a[8 * i + 7]));
      }
      const uint32_t par = pos & 1;
      p2_mma<0>(c, par, acc2a, h);
      __syncwarp();
      if (lane == 0) mbar_arrive(sig);
      p2_mma<1>(c, par, acc2a, h);
      wg_wait<1>(); stage_release(c, 0);
      p2_mma<2>(c, par, acc2a, h);
      wg_wait<1>(); stage_release(c, 1);
      p2_mma<3>(c, par, acc2a, h);
      wg_wait<1>(); stage_release(c, 2);
      p2_mma<4>(c, par, acc2a, h);
      wg_wait<1>(); stage_release(c, 3);
      p2_mma<5>(c, par, acc2a, h);
      wg_wait<1>(); stage_release(c, 4);
    }
    DBG_T(3);
    {
      const int g = lane >> 2, cc = lane & 3;
      const int t0 = m * 128 + warp * 16 + g;
      const uint2 ga = __ldcg(&sc.gate[t0]), gb = __ldcg(&sc.gate[t0 + 8]);
#pragma unroll
      for (int i = 0; i < 32; i++) acc2b[i] = 0.f;
      mbar_wait(bars + B_RB + 24, 0);
      mbar_wait(bars + B_OWN, 0);
      DBG_T(8);
#pragma unroll
      for (int k = 0; k < 4; k++) {
#pragma unroll
        for (int i = 0; i < 4; i++) {
          float4 r = lds128f(lbuf + k * 16384 + i * 512);
          const uint32_t w0 = __float_as_uint(r.x), w1 = __float_as_uint(r.y), w2 = __float_as_uint(r.z), w3 = __float_as_uint(r.w);
          acc2b[8 * i + 0] += bf_lo(w0); acc2b[8 * i + 1] += bf_hi(w0); acc2b[8 * i + 2] += bf_lo(w1); acc2b[8 * i + 3] += bf_hi(w1);
          acc2b[8 * i + 4] += bf_lo(w2); acc2b[8 * i + 5] += bf_hi(w2); acc2b[8 * i + 6] += bf_lo(w3); acc2b[8 * i + 7] += bf_hi(w3);
        }
      }
      float c8[4] = {0.f, 0.f, 0.f, 0.f};
#pragma unroll
      for (int i = 0; i < 8; i++) {
        uint32_t w0, w1;
        asm volatile("ld.shared.v2.u32 {%0,%1}, [%2];" : "=r"(w0), "=r"(w1) : "r"(sb + OFF_C8 + i * 2048 + warp * 256 + lane * 8));
        c8[0] += bf_lo(w0); c8[1] += bf_hi(w0); c8[2] += bf_lo(w1); c8[3] += bf_hi(w1);
      }
      DBG_T(9);
      mbar_wait(bars + B_FULL, 0);
      wg_wait<0>();
      fence_regs(acc2a);
      DBG_T(4);
#pragma unroll
      for (int jj = 0; jj < 4; jj++) {
        uint32_t a[4];
        {
          const int dl = 8 * (2 * jj + (lane >> 4)) + (lane & 7);
          const int chk = 2 * wi + ((lane >> 3) & 1);
          ldsm4t(a, sb + OFF_ST + wg * 8192 + dl * 128 + ((chk ^ (dl & 7)) << 4));
        }
        uint32_t o[4];
#pragma unroll
        for (int e = 0; e < 2; e++) {
          const int q = 2 * jj + e;
          uint32_t bb = lds32(sb + OFF_B2 + (f * 64 + q * 8 + cc * 2) * 2);
          uint32_t v0 = bf2_add(pack_bf16(acc2a[4 * q] + acc2b[4 * q], acc2a[4 * q + 1] + acc2b[4 * q + 1]), bb);
          uint32_t v1 = bf2_add(pack_bf16(acc2a[4 * q + 2] + acc2b[4 * q + 2], acc2a[4 * q + 3] + acc2b[4 * q + 3]), bb);
          o[2 * e] = bf2_add(bf2_mul(ga.x, a[2 * e]), bf2_mul(ga.y, v0));
          o[2 * e + 1] = bf2_add(bf2_mul(gb.x, a[2 * e + 1]), bf2_mul(gb.y, v1));
        }
        {
          const int row = (lane & 7) + ((lane >> 3) & 1) * 8;
          const uint32_t addr = sb + 49152 + warp * 2048 + row * 128 + (((2 * jj + (lane >> 4)) ^ (row & 7)) << 4);
          asm volatile("stmatrix.sync.aligned.m8n8.x4.shared.b16 [%0], {%1,%2,%3,%4};"
                       ::"r"(addr), "r"(o[0]), "r"(o[1]), "r"(o[2]), "r"(o[3]) : "memory");
        }
      }
      asm volatile("fence.proxy.async.shared::cta;" ::: "memory");
      __syncwarp();
      if (lane == 0) {
        asm volatile("cp.async.bulk.tensor.2d.global.shared::cta.bulk_group [%0, {%2, %3}], [%1];\n"
                     "cp.async.bulk.commit_group;"
                     ::"l"(&tm_out), "r"(sb + 49152 + warp * 2048), "r"(f * 64), "r"(m * 128 + warp * 16) : "memory");
      }
      __syncwarp();
      mbar_wait(bars + B_A8, 0);
      {
        __nv_bfloat16* op = ar.out + (size_t)t0 * D_MOD + cc * 2 + 512 + f * 8;
        uint32_t a0, a1;
        const uint32_t addr = sb + OFF_A8 + (lane & 7) * 256 + (warp * 2 + ((lane >> 3) & 1)) * 16;
        asm volatile("ldmatrix.sync.aligned.m8n8.x2.trans.shared.b16 {%0,%1}, [%2];" : "=r"(a0), "=r"(a1) : "r"(addr));
        const uint32_t bb = lds32(sb + OFF_B2 + (512 + f * 8 + cc * 2) * 2);
        const uint32_t v0 = bf2_add(pack_bf16(c8[0], c8[1]), bb), v1 = bf2_add(pack_bf16(c8[2], c8[3]), bb);
        *reinterpret_cast<uint32_t*>(op) = bf2_add(bf2_mul(ga.x, a0), bf2_mul(ga.y, v0));
        *reinterpret_cast<uint32_t*>(op + 8 * D_MOD) = bf2_add(bf2_mul(gb.x, a1), bf2_mul(gb.y, v1));
      }
      if (lane == 0) asm volatile("cp.async.bulk.wait_group.read 0;" ::: "memory");
      DBG_T(5);
      DBG_G(29);
    }
  }
}

typedef CUresult (*EncodeTiledFn)(CUtensorMap*, CUtensorMapDataType, cuuint32_t, void*, const cuuint64_t*,
                                  const cuuint64_t*, const cuuint32_t*, const cuuint32_t*, CUtensorMapInterleave,
                                  CUtensorMapSwizzle, CUtensorMapL2promotion, CUtensorMapFloatOOBfill);

static void make_map(EncodeTiledFn enc, CUtensorMap* tm, const void* base, uint64_t inner, uint64_t outer, uint32_t binner,
                     uint32_t bouter, CUtensorMapSwizzle swz) {
  cuuint64_t gd[2] = {inner, outer};
  cuuint64_t gs[1] = {inner * 2};
  cuuint32_t bd[2] = {binner, bouter};
  cuuint32_t es[2] = {1, 1};
  enc(tm, CU_TENSOR_MAP_DATA_TYPE_BFLOAT16, 2, const_cast<void*>(base), gd, gs, bd, es, CU_TENSOR_MAP_INTERLEAVE_NONE, swz,
      CU_TENSOR_MAP_L2_PROMOTION_L2_128B, CU_TENSOR_MAP_FLOAT_OOB_FILL_NONE);
}

extern "C" void kernel_launch(void* const* d_in, const int* in_sizes, int n_in, void* d_out, int out_size) {
  typedef const __nv_bfloat16* BP;
  Args ar;
  ar.u = (BP)d_in[0]; ar.Are = (BP)d_in[1]; ar.Aim = (BP)d_in[2]; ar.Bre = (BP)d_in[3]; ar.Bim = (BP)d_in[4];
  ar.Cre = (BP)d_in[5]; ar.Cim = (BP)d_in[6]; ar.logdt = (BP)d_in[7]; ar.Dskip = (BP)d_in[8];
  ar.w1 = (BP)d_in[10]; ar.b1 = (BP)d_in[11]; ar.w2 = (BP)d_in[12]; ar.b2 = (BP)d_in[13]; ar.gate_w = (BP)d_in[14];
  ar.out = (__nv_bfloat16*)d_out;

  static EncodeTiledFn enc = nullptr;
  static Scratch sc;
  if (!enc) {
    cudaDriverEntryPointQueryResult qr;
    cudaGetDriverEntryPoint("cuTensorMapEncodeTiled", (void**)&enc, cudaEnableDefault, &qr);
    cudaGetSymbolAddress((void**)&sc.aT, g_aT);
    cudaGetSymbolAddress((void**)&sc.xn, g_xn);
    cudaGetSymbolAddress((void**)&sc.gate, g_gate);
    cudaGetSymbolAddress((void**)&sc.slots, g_slots);
    cudaGetSymbolAddress((void**)&sc.slots8, g_slots8);
    cudaGetSymbolAddress((void**)&sc.flags, g_flags);
    sc.dbg = nullptr;
    cudaFuncSetAttribute(fused_kernel, cudaFuncAttributeMaxDynamicSharedMemorySize, SMEM_BYTES);
  }
  CUtensorMap tm_x, tm_w1, tm_w2, tm_aT, tm_xn, tm_out, tm_a8;
  make_map(enc, &tm_a8, sc.aT, L_SEQ, D_MOD, 128, 8, CU_TENSOR_MAP_SWIZZLE_NONE);
  make_map(enc, &tm_x, ar.u, D_MOD, L_SEQ, 8, 256, CU_TENSOR_MAP_SWIZZLE_NONE);
  make_map(enc, &tm_w2, ar.w2, D_MOD, F_HID, 64, 96, CU_TENSOR_MAP_SWIZZLE_128B);
  make_map(enc, &tm_aT, sc.aT, L_SEQ, D_MOD, 64, 64, CU_TENSOR_MAP_SWIZZLE_128B);
  make_map(enc, &tm_xn, sc.xn, D_MOD, L_SEQ, 64, 128, CU_TENSOR_MAP_SWIZZLE_128B);
  make_map(enc, &tm_out, d_out, D_MOD, L_SEQ, 64, 16, CU_TENSOR_MAP_SWIZZLE_128B);
  {
    cuuint64_t gd[3] = {32, D_MOD, F_HID / 32};
    cuuint64_t gs[2] = {F_HID * 2, 64};
    cuuint32_t bd[3] = {32, 64, 3};
    cuuint32_t es[3] = {1, 1, 1};
    enc(&tm_w1, CU_TENSOR_MAP_DATA_TYPE_BFLOAT16, 3, (void*)ar.w1, gd, gs, bd, es, CU_TENSOR_MAP_INTERLEAVE_NONE,
        CU_TENSOR_MAP_SWIZZLE_64B, CU_TENSOR_MAP_L2_PROMOTION_L2_128B, CU_TENSOR_MAP_FLOAT_OOB_FILL_NONE);
  }
  fused_kernel<<<132, 512, SMEM_BYTES, cudaStreamPerThread>>>(tm_x, tm_w1, tm_w2, tm_aT, tm_xn, tm_out, tm_a8, ar, sc);
}
```

```cpp
#include <cuda_runtime.h>
#include <cuda_bf16.h>
#include <cuda.h>
#include <stdint.h>

#define HFENCE() asm volatile("fence.proxy.async.shared::cta;" ::: "memory")
#define L_SEQ 2048
#define D_MOD 576
#define F_HID 4608
#define N_ST 128

__device__ __align__(1024) __nv_bfloat16 g_aT[D_MOD * L_SEQ];
__device__ __align__(1024) __nv_bfloat16 g_xn[L_SEQ * D_MOD];
__device__ __align__(1024) uint32_t g_slots[16 * 8 * 3 * 4096];
__device__ __align__(1024) uint32_t g_slots8[16 * 8 * 4096];
__device__ uint2 g_gate[L_SEQ];
__device__ unsigned int g_flags[832];
struct Scratch {
  __nv_bfloat16* aT; __nv_bfloat16* xn; uint2* gate; uint32_t* slots; uint32_t* slots8; unsigned int* flags;
  long long* dbg;
};
#define DBG_T(i)
#define DBG_S(i)
#define DBG_H(i)
#define DBG_G(i)

__device__ __forceinline__ uint32_t smem_u32(const void* p) { return (uint32_t)__cvta_generic_to_shared(p); }
__device__ __forceinline__ void mbar_init(uint32_t bar, int cnt) {
  asm volatile("mbarrier.init.shared::cta.b64 [%0], %1;" ::"r"(bar), "r"(cnt));
}
__device__ __forceinline__ void mbar_expect_tx(uint32_t bar, uint32_t bytes) {
  asm volatile("mbarrier.arrive.expect_tx.shared::cta.b64 _, [%0], %1;" ::"r"(bar), "r"(bytes) : "memory");
}
__device__ __forceinline__ void mbar_arrive(uint32_t bar) {
  asm volatile("mbarrier.arrive.shared::cta.b64 _, [%0];" ::"r"(bar) : "memory");
}
__device__ __forceinline__ void mbar_arrive_remote(uint32_t remote_bar) {
  asm volatile("mbarrier.arrive.relaxed.cluster.shared::cluster.b64 _, [%0];" ::"r"(remote_bar) : "memory");
}
__device__ __forceinline__ void mbar_wait(uint32_t bar, uint32_t parity) {
  asm volatile(
      "{\n.reg .pred p;\n.reg .u32 n;\nmov.u32 n, 0;\n"
      "W_%=:\nmbarrier.try_wait.parity.shared::cta.b64 p, [%0], %1;\n@p bra D_%=;\n"
      "add.u32 n, n, 1;\nsetp.lt.u32 p, n, 400000;\n@p bra W_%=;\ntrap;\nD_%=:\n}"
      ::"r"(bar), "r"(parity) : "memory");
}
__device__ __forceinline__ void tma2d(uint32_t dst, const CUtensorMap* tm, int c0, int c1, uint32_t bar) {
  asm volatile("cp.async.bulk.tensor.2d.shared::cluster.global.mbarrier::complete_tx::bytes [%0], [%1, {%3, %4}], [%2];"
               ::"r"(dst), "l"(tm), "r"(bar), "r"(c0), "r"(c1) : "memory");
}
__device__ __forceinline__ void wait_flag(unsigned int* flag, unsigned int target) {
  asm volatile(
      "{\n.reg .pred p;\n.reg .u32 n, v;\nmov.u32 n, 0;\n"
      "W_%=:\nld.acquire.gpu.global.u32 v, [%0];\nsetp.ge.u32 p, v, %1;\n@p bra D_%=;\n"
      "nanosleep.u32 32;\nadd.u32 n, n, 1;\nsetp.lt.u32 p, n, 4000000;\n@p bra W_%=;\ntrap;\nD_%=:\n}"
      ::"l"(flag), "r"(target) : "memory");
}
__device__ __forceinline__ void bulk_g2s(uint32_t dst, const void* src, uint32_t bytes, uint32_t bar) {
  asm volatile("cp.async.bulk.shared::cluster.global.mbarrier::complete_tx::bytes [%0], [%1], %2, [%3];"
               ::"r"(dst), "l"(src), "r"(bytes), "r"(bar) : "memory");
}
__device__ __forceinline__ void tma3d(uint32_t dst, const CUtensorMap* tm, int c0, int c1, int c2, uint32_t bar) {
  asm volatile("cp.async.bulk.tensor.3d.shared::cluster.global.mbarrier::complete_tx::bytes [%0], [%1, {%3, %4, %5}], [%2];"
               ::"r"(dst), "l"(tm), "r"(bar), "r"(c0), "r"(c1), "r"(c2) : "memory");
}
__device__ __forceinline__ uint32_t mapa(uint32_t addr, uint32_t rank) {
  uint32_t r;
  asm("mapa.shared::cluster.u32 %0, %1, %2;" : "=r"(r) : "r"(addr), "r"(rank));
  return r;
}
__device__ __forceinline__ float4 lds128f(uint32_t addr) {
  float4 v;
  asm volatile("ld.shared.v4.f32 {%0,%1,%2,%3}, [%4];" : "=f"(v.x), "=f"(v.y), "=f"(v.z), "=f"(v.w) : "r"(addr));
  return v;
}
__device__ __forceinline__ uint32_t lds32(uint32_t addr) {
  uint32_t v;
  asm volatile("ld.shared.u32 %0, [%1];" : "=r"(v) : "r"(addr));
  return v;
}
__device__ __forceinline__ void sts128(uint32_t addr, uint32_t a, uint32_t b, uint32_t c, uint32_t d) {
  asm volatile("st.shared.v4.u32 [%0], {%1,%2,%3,%4};" ::"r"(addr), "r"(a), "r"(b), "r"(c), "r"(d) : "memory");
}
#define WG_FENCE() asm volatile("wgmma.fence.sync.aligned;" ::: "memory")
#define WG_COMMIT() asm volatile("wgmma.commit_group.sync.aligned;" ::: "memory")
template <int n> __device__ __forceinline__ void wg_wait() {
  asm volatile("wgmma.wait_group.sync.aligned %0;" ::"n"(n) : "memory");
}
__device__ __forceinline__ uint32_t pack_bf16(float lo, float hi) {
  uint32_t r;
  asm("cvt.rn.bf16x2.f32 %0, %1, %2;" : "=r"(r) : "f"(hi), "f"(lo));
  return r;
}
__device__ __forceinline__ float bf_lo(uint32_t p) { return __uint_as_float(p << 16); }
__device__ __forceinline__ float bf_hi(uint32_t p) { return __uint_as_float(p & 0xffff0000u); }
__device__ __forceinline__ float bf_round(float x) { return __bfloat162float(__float2bfloat16_rn(x)); }
__device__ __forceinline__ uint32_t bf2_add(uint32_t a, uint32_t b) {
  uint32_t r;
  asm("add.rn.bf16x2 %0, %1, %2;" : "=r"(r) : "r"(a), "r"(b));
  return r;
}
__device__ __forceinline__ uint32_t bf2_mul(uint32_t a, uint32_t b) {
  uint32_t r;
  asm("mul.rn.bf16x2 %0, %1, %2;" : "=r"(r) : "r"(a), "r"(b));
  return r;
}
__device__ __forceinline__ uint32_t bf2_fma(uint32_t a, uint32_t b, uint32_t c) {
  uint32_t r;
  asm("fma.rn.bf16x2 %0, %1, %2, %3;" : "=r"(r) : "r"(a), "r"(b), "r"(c));
  return r;
}
__device__ __forceinline__ uint32_t gelu_pack(float a0, float a1, uint32_t hbias2) {
  const uint32_t hp = bf2_fma(pack_bf16(a0, a1), 0x3f003f00u, hbias2);
  const uint32_t q = bf2_fma(bf2_mul(hp, hp), 0x3e923e92u  , 0x3fcc3fccu  );
  uint32_t t;
  asm("tanh.approx.bf16x2 %0, %1;" : "=r"(t) : "r"(bf2_mul(hp, q)));
  return bf2_fma(hp, t, hp);
}

#define R8(a, o) "+f"(a[o]), "+f"(a[o + 1]), "+f"(a[o + 2]), "+f"(a[o + 3]), "+f"(a[o + 4]), "+f"(a[o + 5]), "+f"(a[o + 6]), "+f"(a[o + 7])
#define W8(a, o) "=f"(a[o]), "=f"(a[o + 1]), "=f"(a[o + 2]), "=f"(a[o + 3]), "=f"(a[o + 4]), "=f"(a[o + 5]), "=f"(a[o + 6]), "=f"(a[o + 7])
#define REGS48 "{%0,%1,%2,%3,%4,%5,%6,%7,%8,%9,%10,%11,%12,%13,%14,%15,%16,%17,%18,%19,%20,%21,%22,%23," \
               "%24,%25,%26,%27,%28,%29,%30,%31,%32,%33,%34,%35,%36,%37,%38,%39,%40,%41,%42,%43,%44,%45,%46,%47}"
#define REGS32 "{%0,%1,%2,%3,%4,%5,%6,%7,%8,%9,%10,%11,%12,%13,%14,%15,%16,%17,%18,%19,%20,%21,%22,%23," \
               "%24,%25,%26,%27,%28,%29,%30,%31}"
#define DESC_HI_A  "0x40000040"
#define DESC_HI_B1 "0x80000020"
#define DESC_HI_B2 "0x40000040"
template <bool ACC, int OA, int OB>
__device__ __forceinline__ void wgmma_ss_n96(float (&d)[48], uint32_t da, uint32_t db) {
  if (ACC)
    asm volatile("{\n.reg .b64 xa, xb;\n.reg .b32 la, lb;\nadd.u32 la, %48, %50;\nadd.u32 lb, %49, %51;\n"
                 "mov.b64 xa, {la, " DESC_HI_A "};\nmov.b64 xb, {lb, " DESC_HI_B1 "};\n"
                 "wgmma.mma_async.sync.aligned.m64n96k16.f32.bf16.bf16 " REGS48 ", xa, xb, 1, 1, 1, 0, 1;\n}\n"
                 : R8(d, 0), R8(d, 8), R8(d, 16), R8(d, 24), R8(d, 32), R8(d, 40) : "r"(da), "r"(db), "n"(OA), "n"(OB));
  else
    asm volatile("{\n.reg .b64 xa, xb;\n.reg .b32 la, lb;\nadd.u32 la, %48, %50;\nadd.u32 lb, %49, %51;\n"
                 "mov.b64 xa, {la, " DESC_HI_A "};\nmov.b64 xb, {lb, " DESC_HI_B1 "};\n"
                 "wgmma.mma_async.sync.aligned.m64n96k16.f32.bf16.bf16 " REGS48 ", xa, xb, 0, 1, 1, 0, 1;\n}\n"
                 : W8(d, 0), W8(d, 8), W8(d, 16), W8(d, 24), W8(d, 32), W8(d, 40) : "r"(da), "r"(db), "n"(OA), "n"(OB));
}
template <bool ACC, int OB>
__device__ __forceinline__ void wgmma_rs_n64(float (&d)[32], uint32_t a0, uint32_t a1, uint32_t a2, uint32_t a3, uint32_t db) {
  if (ACC)
    asm volatile("{\n.reg .b64 xb;\n.reg .b32 lb;\nadd.u32 lb, %36, %37;\nmov.b64 xb, {lb, " DESC_HI_B2 "};\n"
                 "wgmma.mma_async.sync.aligned.m64n64k16.f32.bf16.bf16 " REGS32 ", {%32,%33,%34,%35}, xb, 1, 1, 1, 1;\n}\n"
                 : R8(d, 0), R8(d, 8), R8(d, 16), R8(d, 24) : "r"(a0), "r"(a1), "r"(a2), "r"(a3), "r"(db), "n"(OB));
  else
    asm volatile("{\n.reg .b64 xb;\n.reg .b32 lb;\nadd.u32 lb, %36, %37;\nmov.b64 xb, {lb, " DESC_HI_B2 "};\n"
                 "wgmma.mma_async.sync.aligned.m64n64k16.f32.bf16.bf16 " REGS32 ", {%32,%33,%34,%35}, xb, 0, 1, 1, 1;\n}\n"
                 : W8(d, 0), W8(d, 8), W8(d, 16), W8(d, 24) : "r"(a0), "r"(a1), "r"(a2), "r"(a3), "r"(db), "n"(OB));
}
template <int N> __device__ __forceinline__ void fence_regs(float (&d)[N]) {
#pragma unroll
  for (int i = 0; i < N; i++) asm volatile("" : "+f"(d[i])::"memory");
}

constexpr int XS_BYTES = 9 * 16384;
constexpr int STAGE_BYTES = 12288;
constexpr int OFF_ST = XS_BYTES;
constexpr int OFF_B1 = OFF_ST + 6 * STAGE_BYTES;
constexpr int OFF_B2 = OFF_B1 + 1152;
constexpr int OFF_BAR = OFF_B2 + 1152;
constexpr int B_FULL = 0, B_X = 48  , B_RB = 120  , B_OWN = 152, B_FIN = 160, B_A8 = 168, B_OWN2 = 176,
              B_EMPTY = 184  , B_TS = 232  , B_TS8 = 264, B_TR = 272  , B_P1L = 296, B_P1R = 304, B_U = 312,
              B_U0 = 320, NBARS = 41,
              B_CONV = 328, B_COMB = 336;
constexpr int OFF_A8 = OFF_BAR + 512;
constexpr int OFF_ARGS = OFF_A8 + 2048;
constexpr int SMEM_BYTES = OFF_ARGS + 256 + 1024;
constexpr int OFF_STG = 65536, OFF_C8 = 131072;
constexpr int E_UA = 0, E_UB = 3616, E_W3A = 7232, E_W3B = 10848, E_W5 = 14464, E_W9 = 17568, E_TAP = 19680, E_SIZE = 23392;
constexpr int L_W7 = 4752, L_KB = 6832, L_Y = 6848, L_YB = 8304, L_SIZE = 28656;
constexpr int L_CONST = L_Y, L_KC = L_Y + 10240;
constexpr int TP_0 = 0, TP_W3A = 580, TP_UA = 716, TP_UB = 852, TP_W3B = 988, TP_W5 = 1248, TP_W9 = 1448, TP_W7 = 1648,
              TP_COPY = 1856;
__device__ __forceinline__ int e_off(int ch) { return ch == 0 ? 0 : OFF_ST + (ch - 1) * E_SIZE; }
__device__ __forceinline__ int l_off(int ch) { return 32768 + ch * L_SIZE; }
__device__ __forceinline__ int xg_off(int box) { return box < 4 ? OFF_ST + box * 4096 : 170880 + (box - 4) * 4096; }

__device__ __forceinline__ void ln_load(const __nv_bfloat16* __restrict__ x, const __nv_bfloat16* __restrict__ gate_w,
                                        int row, int lane, uint32_t (&w)[9], uint32_t (&gw)[9]) {
  const uint32_t* xr = reinterpret_cast<const uint32_t*>(x + (size_t)row * D_MOD) + lane;
  const uint32_t* gwp = reinterpret_cast<const uint32_t*>(gate_w) + lane;
#pragma unroll
  for (int j = 0; j < 9; j++) {
    asm volatile("ld.global.nc.u32 %0, [%1];" : "=r"(w[j]) : "l"(xr + j * 32));
    asm volatile("ld.global.nc.u32 %0, [%1];" : "=r"(gw[j]) : "l"(gwp + j * 32));
  }
}
__device__ __forceinline__ void ln_row(int row, int lane, const Scratch& sc, const uint32_t (&w)[9], const uint32_t (&gw)[9]) {
  float s = 0.f, gsum = 0.f;
#pragma unroll
  for (int j = 0; j < 9; j++) {
    uint32_t pr2 = bf2_mul(w[j], gw[j]);
    s += bf_lo(w[j]) + bf_hi(w[j]);
    gsum += bf_lo(pr2) + bf_hi(pr2);
  }
#pragma unroll
  for (int o = 1; o < 32; o <<= 1) { s += __shfl_xor_sync(~0u, s, o); gsum += __shfl_xor_sync(~0u, gsum, o); }
  const float mean = s * (1.0f / 576.0f);
  float vs = 0.f;
#pragma unroll
  for (int j = 0; j < 9; j++) {
    float d0 = bf_lo(w[j]) - mean, d1 = bf_hi(w[j]) - mean;
    vs = fmaf(d0, d0, vs); vs = fmaf(d1, d1, vs);
  }
#pragma unroll
  for (int o = 1; o < 32; o <<= 1) vs += __shfl_xor_sync(~0u, vs, o);
  const float mb = bf_round(mean);
  const float vb = bf_round(vs * (1.0f / 576.0f));
  const float rinv = __frcp_rn(bf_round(__fsqrt_rn(bf_round(vb + 1e-5f))));
  const uint32_t nm2 = pack_bf16(-mb, -mb);
  uint32_t* dst = reinterpret_cast<uint32_t*>(sc.xn + (size_t)row * D_MOD) + lane;
#pragma unroll
  for (int j = 0; j < 9; j++) {
    uint32_t dd = bf2_add(w[j], nm2);
    dst[j * 32] = pack_bf16(bf_lo(dd) * rinv, bf_hi(dd) * rinv);
  }
  if (lane == 0) {
    float gv = bf_round(__fdividef(1.0f, 1.0f + __expf(-bf_round(gsum))));
    float og = bf_round(1.0f - gv);
    sc.gate[row] = make_uint2(pack_bf16(gv, gv), pack_bf16(og, og));
  }
}
__device__ __forceinline__ void mma_bf16(float (&d)[4], uint32_t a0, uint32_t a1, uint32_t a2, uint32_t a3, uint32_t b0, uint32_t b1) {
  asm("mma.sync.aligned.m16n8k16.row.col.f32.bf16.bf16.f32 {%0,%1,%2,%3}, {%4,%5,%6,%7}, {%8,%9}, {%0,%1,%2,%3};"
      : "+f"(d[0]), "+f"(d[1]), "+f"(d[2]), "+f"(d[3]) : "r"(a0), "r"(a1), "r"(a2), "r"(a3), "r"(b0), "r"(b1));
}
__device__ __forceinline__ void mma_tf32(float (&d)[4], float a0, float a1, float a2, float a3, float b0, float b1) {
  asm("mma.sync.aligned.m16n8k8.row.col.f32.tf32.tf32.f32 {%0,%1,%2,%3}, {%4,%5,%6,%7}, {%8,%9}, {%0,%1,%2,%3};"
      : "+f"(d[0]), "+f"(d[1]), "+f"(d[2]), "+f"(d[3])
      : "r"(__float_as_uint(a0)), "r"(__float_as_uint(a1)), "r"(__float_as_uint(a2)), "r"(__float_as_uint(a3)),
        "r"(__float_as_uint(b0)), "r"(__float_as_uint(b1)));
}
__device__ __forceinline__ float2 cexp_l(float al, float th, float l) {
  float mg;
  asm("ex2.approx.ftz.f32 %0, %1;" : "=f"(mg) : "f"(al * l));
  const float tr = th * l;
  return make_float2(mg * __cosf(tr), mg * __sinf(tr));
}
__device__ __forceinline__ float2 cmul(float2 a, float2 b) {
  return make_float2(fmaf(a.x, b.x, -a.y * b.y), fmaf(a.x, b.y, a.y * b.x));
}
__device__ __forceinline__ float2 cmulc(float2 a, float2 b) {
  return make_float2(fmaf(a.x, b.x, -a.y * b.y), fmaf(-a.x, b.y, -a.y * b.x));
}
__device__ __forceinline__ float2 csq(float2 a) { return make_float2(fmaf(a.x, a.x, -a.y * a.y), 2.0f * a.x * a.y); }
#define SM_U32(p) (*reinterpret_cast<uint32_t*>(p))
#define SM_F32(p) (*reinterpret_cast<float*>(p))
#define SM_U16(p) (*reinterpret_cast<unsigned short*>(p))
#define SM_U2(p) (*reinterpret_cast<uint2*>(p))
#define SM_F2(p) (*reinterpret_cast<float2*>(p))
#define SM_U4(p) (*reinterpret_cast<uint4*>(p))
#define SM_F4(p) (*reinterpret_cast<float4*>(p))
template <int OFF, int TAG>
__device__ __forceinline__ uint32_t lds_free(uint32_t base) {
  uint32_t v;
  asm volatile("ld.volatile.shared.u32 %0, [%1+%2]; // %3" : "=r"(v) : "r"(base), "n"(OFF), "n"(TAG));
  return v;
}
template <int K0, int K1, int OFF, int K>
__device__ __forceinline__ void load_tquads_(uint32_t (&q)[K1 - K0][4], uint32_t tp) {
  if constexpr (K >= K0) {
    q[K - K0][0] = lds_free<OFF - 32 * K, 0>(tp);
    q[K - K0][1] = lds_free<OFF - 32 * K - 16, 1>(tp);
    q[K - K0][2] = lds_free<OFF - 32 * K + 16, 2>(tp);
    q[K - K0][3] = lds_free<OFF - 32 * K, 3>(tp);
    load_tquads_<K0, K1, OFF, K - 1>(q, tp);
  }
}
template <int K0, int K1, int OFF>
__device__ __forceinline__ void load_tquads(uint32_t (&q)[K1 - K0][4], uint32_t tp) {
  load_tquads_<K0, K1, OFF, K1 - 1>(q, tp);
}
__device__ __forceinline__ void ldsm4_free(uint32_t (&r)[4], uint32_t addr) {
  asm("ldmatrix.sync.aligned.m8n8.x4.shared.b16 {%0,%1,%2,%3}, [%4];"
      : "=r"(r[0]), "=r"(r[1]), "=r"(r[2]), "=r"(r[3]) : "r"(addr));
}
__device__ __forceinline__ void ldsm4t_free(uint32_t (&r)[4], uint32_t addr) {
  asm("ldmatrix.sync.aligned.m8n8.x4.trans.shared.b16 {%0,%1,%2,%3}, [%4];"
      : "=r"(r[0]), "=r"(r[1]), "=r"(r[2]), "=r"(r[3]) : "r"(addr));
}
__device__ __forceinline__ uint32_t ldg_u16(const __nv_bfloat16* p) {
  unsigned short v;
  asm volatile("ld.global.nc.u16 %0, [%1];" : "=h"(v) : "l"(p));
  return v;
}
__device__ __forceinline__ void ldsm4t(uint32_t (&r)[4], uint32_t addr) {
  asm volatile("ldmatrix.sync.aligned.m8n8.x4.trans.shared.b16 {%0,%1,%2,%3}, [%4];"
               : "=r"(r[0]), "=r"(r[1]), "=r"(r[2]), "=r"(r[3]) : "r"(addr) : "memory");
}
template <int I0, int I1, int K0, int K1, int JMIN, int RB, int TOFF>
__device__ __forceinline__ void band(float (&acc)[I1 - I0][4], uint32_t tp, uint32_t sa, uint32_t za, int lane) {
  uint32_t tq[K1 - K0][4];
  load_tquads<K0, K1, TOFF>(tq, tp);
  constexpr int JL = (I0 - K1 + 1 > JMIN) ? I0 - K1 + 1 : JMIN, JH = I1 - 1 - K0;
  constexpr int JP = (JL >= 0) ? (JL & ~1) : -2;
#pragma unroll
  for (int J2 = JP; J2 <= JH; J2 += 2) {
    uint32_t b[4];
    ldsm4t_free(b, (J2 < 0 && lane < 31) ? za : sa + J2 * 16 * RB);
#pragma unroll
    for (int hf = 0; hf < 2; hf++) {
      const int J = J2 + hf;
#pragma unroll
      for (int k = K0; k < K1; k++) {
        const int I = J + k;
        if (J >= JL && J <= JH && I >= I0 && I < I1)
          mma_bf16(acc[I - I0], tq[k - K0][0], tq[k - K0][1], tq[k - K0][2], tq[k - K0][3], b[2 * hf], b[2 * hf + 1]);
      }
    }
  }
}
template <int I0, int I1>
__device__ __forceinline__ void p8_tiles(uint32_t ea, uint32_t za, char* lb, uint32_t tp, int lane) {
  float acc[I1 - I0][4];
#pragma unroll
  for (int i = 0; i < I1 - I0; i++) { acc[i][0] = acc[i][1] = acc[i][2] = acc[i][3] = 0.f; }
  const uint32_t sa = ea + 32 + lane * 16;
  band<I0, I1, 2, 5, -1, 16, TP_W3A + 160>(acc, tp, sa + E_W3A, za, lane);
  band<I0, I1, 2, 5, 0, 16, TP_UA + 160>(acc, tp, sa + E_UA, za, lane);
  band<I0, I1, 2, 5, 0, 16, TP_UB + 160>(acc, tp, sa + E_UB, za, lane);
  band<I0, I1, 2, 9, 0, 16, TP_W3B + 288>(acc, tp, sa + E_W3B, za, lane);
  band<I0, I1, 4, 9, -1, 16, TP_W5 + 288>(acc, tp, sa + E_W5, za, lane);
  char* a = lb + L_Y + L_YB + 4 * (8 * (lane >> 2) + 2 * (lane & 3));
#pragma unroll
  for (int I = I0; I < I1; I++) {
    SM_F2(a + 4 * (128 * I + 4 * (I >> 1))) = make_float2(acc[I - I0][0], acc[I - I0][1]);
    SM_F2(a + 4 * (128 * I + 4 * (I >> 1)) + 256) = make_float2(acc[I - I0][2], acc[I - I0][3]);
  }
}

struct MlpCtx {
  uint32_t bars;
  uint32_t dA, dB;
  int lane;
};
__device__ __forceinline__ void stage_release(const MlpCtx& c, int slot) {
  if (c.lane == 0) mbar_arrive(c.bars + B_EMPTY + 8 * slot);
}
template <int P>
__device__ __forceinline__ void gelu_part(uint32_t baddr, float (&acc)[48]) {
  asm volatile("" : R8(acc, P * 8)::"memory");
  const uint32_t b0 = bf2_mul(lds32(baddr + P * 32), 0x3f003f00u), b1 = bf2_mul(lds32(baddr + P * 32 + 16), 0x3f003f00u);
  uint32_t r0 = gelu_pack(acc[P * 8 + 0], acc[P * 8 + 1], b0);
  uint32_t r1 = gelu_pack(acc[P * 8 + 2], acc[P * 8 + 3], b0);
  uint32_t r2 = gelu_pack(acc[P * 8 + 4], acc[P * 8 + 5], b1);
  uint32_t r3 = gelu_pack(acc[P * 8 + 6], acc[P * 8 + 7], b1);
  acc[P * 8 + 0] = __uint_as_float(r0);
  acc[P * 8 + 1] = __uint_as_float(r1);
  acc[P * 8 + 2] = __uint_as_float(r2);
  acc[P * 8 + 3] = __uint_as_float(r3);
}
__device__ __forceinline__ void h_push(uint32_t (&h)[144], float (&acc)[48]) {
  asm volatile("" : R8(acc, 0)::"memory");
#pragma unroll
  for (int i = 0; i < 96; i++) h[i] = h[i + 24];
#pragma unroll
  for (int i = 0; i < 24; i++) h[96 + i] = __float_as_uint(acc[(i >> 2) * 8 + (i & 3)]);
}
template <int SB, int I>
__device__ __forceinline__ void p1_mma(const MlpCtx& c, float (&cur)[48]) {
  constexpr int S = SB % 9;
  wgmma_ss_n96<(S | I) != 0, ((S * 16384 + I * 32) >> 4),
               (4096 >> 4 << 16) + (((SB % 6) * STAGE_BYTES + I * 1024) >> 4)>(cur, c.dA, c.dB);
}
template <int SB>
__device__ __forceinline__ void p1_stage(const MlpCtx& c, int j, uint32_t baddr, float (&cur)[48], float (&prev)[48],
                                         uint32_t (&h)[144]) {
  constexpr int S = SB % 9;
  if (SB < 9) mbar_wait(c.bars + B_X + 8 * S, 0);
  mbar_wait(c.bars + B_FULL + 8 * (SB % 6), ((SB / 6) + j) & 1);
  WG_FENCE();
  p1_mma<SB, 0>(c, cur); p1_mma<SB, 1>(c, cur); p1_mma<SB, 2>(c, cur); p1_mma<SB, 3>(c, cur);
  WG_COMMIT();
  if (S >= 1 && S <= 6) gelu_part<(S >= 1 && S <= 6) ? S - 1 : 0>(baddr, prev);
  if (S == 7) h_push(h, prev);
  wg_wait<1>();
  if (SB > 0 || j > 0) stage_release(c, (SB + 5) % 6);
  if (S == 0) fence_regs(prev);
}
template <int SB0>
__device__ __forceinline__ void p1_chunk(const MlpCtx& c, int j, uint32_t baddr, float (&cur)[48], float (&prev)[48],
                                         uint32_t (&h)[144]) {
  p1_stage<SB0 + 0>(c, j, baddr, cur, prev, h); p1_stage<SB0 + 1>(c, j, baddr, cur, prev, h);
  p1_stage<SB0 + 2>(c, j, baddr, cur, prev, h); p1_stage<SB0 + 3>(c, j, baddr, cur, prev, h);
  p1_stage<SB0 + 4>(c, j, baddr, cur, prev, h); p1_stage<SB0 + 5>(c, j, baddr, cur, prev, h);
  p1_stage<SB0 + 6>(c, j, baddr, cur, prev, h); p1_stage<SB0 + 7>(c, j, baddr, cur, prev, h);
  p1_stage<SB0 + 8>(c, j, baddr, cur, prev, h);
}
template <int S, int I>
__device__ __forceinline__ void p2_one(const MlpCtx& c, float (&cur)[32], uint32_t (&h)[144]) {
  constexpr int kk = 6 * S + I;
  wgmma_rs_n64<(S | I) != 0, ((S * STAGE_BYTES + I * 2048) >> 4)>(cur, h[4 * kk], h[4 * kk + 1], h[4 * kk + 2], h[4 * kk + 3], c.dB);
}
template <int S>
__device__ __forceinline__ void p2_mma(const MlpCtx& c, uint32_t parity, float (&cur)[32], uint32_t (&h)[144]) {
  mbar_wait(c.bars + B_FULL + 8 * S, parity);
  WG_FENCE();
  p2_one<S, 0>(c, cur, h); p2_one<S, 1>(c, cur, h); p2_one<S, 2>(c, cur, h);
  p2_one<S, 3>(c, cur, h); p2_one<S, 4>(c, cur, h); p2_one<S, 5>(c, cur, h);
  WG_COMMIT();
}
__device__ __forceinline__ int chunk_of(int pos, int pr, int rank) {
  const int off = (int)(0x03231201ull >> (4 * pos)) & 3;
  const int mine = (0x168 >> pos) & 1;
  return pos == 1 ? 8 : 2 * ((pr + off) & 3) + (mine ? rank : rank ^ 1);
}
__device__ __forceinline__ void bulk_s2peer(uint32_t rdst, uint32_t src, uint32_t bytes, uint32_t rbar) {
  asm volatile("cp.async.bulk.shared::cluster.shared::cta.mbarrier::complete_tx::bytes [%0], [%1], %2, [%3];"
               ::"r"(rdst), "r"(src), "r"(bytes), "r"(rbar) : "memory");
}
__device__ __forceinline__ void bulk_s2g_release(void* gdst, uint32_t src, uint32_t bytes) {
  asm volatile("cp.async.bulk.global.shared::cta.bulk_group [%0], [%1], %2;\n"
               "cp.async.bulk.commit_group;\ncp.async.bulk.wait_group 0;\nfence.acq_rel.gpu;"
               ::"l"(gdst), "r"(src), "r"(bytes) : "memory");
}
struct Args {
  const __nv_bfloat16 *u, *Are, *Aim, *Bre, *Bim, *Cre, *Cim, *logdt, *Dskip, *gate_w, *w1, *w2, *b1, *b2;
  __nv_bfloat16* out;
};

struct Maps { const CUtensorMap *x, *w1, *xn; };
__device__ __forceinline__ void load_params(uint32_t (&v)[8], const Args& ar, int d, int n) {
  const int idx = d * N_ST + n;
  v[0] = ldg_u16(ar.Are + idx); v[1] = ldg_u16(ar.Aim + idx); v[2] = ldg_u16(ar.Bre + idx); v[3] = ldg_u16(ar.Bim + idx);
  v[4] = ldg_u16(ar.Cre + idx); v[5] = ldg_u16(ar.Cim + idx); v[6] = ldg_u16(ar.logdt + d); v[7] = ldg_u16(ar.Dskip + d);
}
__device__ __forceinline__ uint4 pack_params(uint32_t (&v)[8]) {
  asm volatile("" : "+r"(v[0]), "+r"(v[1]), "+r"(v[2]), "+r"(v[3]), "+r"(v[4]), "+r"(v[5]), "+r"(v[6]), "+r"(v[7])::"memory");
  return make_uint4(v[0] | (v[1] << 16), v[2] | (v[3] << 16), v[4] | (v[5] << 16), v[6] | (v[7] << 16));
}
__device__ __noinline__ uint4 ssm_pass(const Maps tm, char* sm, const int d0, const int pass, const uint4 pv
) {
  const Args& ar = *reinterpret_cast<const Args*>(sm + OFF_ARGS);
  const Scratch& sc = *reinterpret_cast<const Scratch*>(sm + OFF_ARGS + 128);
  const uint32_t sb = smem_u32(sm), bars = sb + OFF_BAR;
  const int tid = threadIdx.x, lane = tid & 31;
  const int warp = __shfl_sync(0xffffffffu, tid >> 5, 0);
  const int bid = blockIdx.x, m = bid >> 3, f = bid & 7;
  const int g = lane >> 2, cc = lane & 3;
  const int ch = warp >> 2, n = tid & 127;
  char* eb = sm + e_off(ch);
  char* lb = sm + l_off(ch);
#define CH_SYNC() asm volatile("bar.sync %0, 128;" ::"r"(ch + 1) : "memory")
  const bool lead = warp < 8;
  {
    const float are = bf_lo(pv.x), aim = bf_hi(pv.x), bre = bf_lo(pv.y), bim = bf_hi(pv.y);
    const float cre = bf_lo(pv.z), cim = bf_hi(pv.z), ldt = bf_lo(pv.w), dsk = bf_hi(pv.w);
    const float dt = bf_round(expf(ldt));
    const float al = (dt * are) * 1.4426950408889634f, th = dt * aim;
    constexpr float TF32_UNBIAS = 1.0f + 0.7f / 1024.0f;
    const float2 c0 = cmul(make_float2(cre * TF32_UNBIAS, cim * TF32_UNBIAS), make_float2(dt * bre, dt * bim));
    const float2 e64 = cexp_l(al, th, 64.f), e128 = csq(e64), e256 = cexp_l(al, th, 256.f), e512 = csq(e256);
    const float2 k128 = cmul(c0, e128), k256 = cmul(c0, e256), k384 = cmul(k256, e128);
    const float2 k512 = cmul(c0, e512), k516 = cmul(k512, cexp_l(al, th, 4.f));
    const float2 e1024 = cexp_l(al, th, 1024.f), k1024 = cmul(c0, e1024);
    float k2048 = fmaf(k1024.x, e1024.x, -k1024.y * e1024.y) * (1.0f / TF32_UNBIAS);
    char* ca = lb + L_CONST + n * 80;
    SM_F4(ca) = make_float4(al, th, e64.x, e64.y);
    SM_F4(ca + 16) = make_float4(c0.x, c0.y, k128.x, k128.y);
    SM_F4(ca + 32) = make_float4(k256.x, k256.y, k384.x, k384.y);
    SM_F4(ca + 48) = make_float4(k512.x, k512.y, k516.x, k516.y);
    SM_F2(ca + 64) = k1024;
#pragma unroll
    for (int o = 16; o > 0; o >>= 1) k2048 += __shfl_xor_sync(~0u, k2048, o);
    if (lane == 0) SM_F32(lb + L_KC + (warp & 3) * 2576 + 2560) = k2048;
    if (n == 0) SM_F32(lb + L_KB + 8) = dsk;
    __syncwarp();
    DBG_S(0);
    float kd[5][4];
#pragma unroll
    for (int t = 0; t < 5; t++) { kd[t][0] = kd[t][1] = kd[t][2] = kd[t][3] = 0.f; }
    const float l1 = (float)g, l128 = (float)(128 * g);
    const char* cr = lb + L_CONST + ((warp & 3) * 32 + cc) * 80;
    const int o2 = 32 + (g >> 2) * 8, o3 = 48 + (g & 1) * 8, s2 = ((g & 3) << 2) | cc, s3 = ((g >> 1) << 2) | cc;
#pragma unroll 2
    for (int st = 0; st < 8; st++, cr += 320) {
      const float4 q0 = *(const float4*)cr, q1 = *(const float4*)(cr + 16);
      const float2 q2 = *(const float2*)(cr + o2), q3 = *(const float2*)(cr + o3), q4 = *(const float2*)(cr + 64);
      const float2 p1 = cexp_l(q0.x, q0.y, l1), p128 = cexp_l(q0.x, q0.y, l128);
      const float2 p2 = csq(p1), p8 = csq(csq(p2));
      const float2 a1 = cmul(p8, make_float2(q0.z, q0.w));
      float2 x = cmulc(make_float2(q1.x, q1.y), p1);
      mma_tf32(kd[0], p8.x, a1.x, p8.y, a1.y, x.x, x.y);
      x = cmulc(make_float2(q1.z, q1.w), p1);
      mma_tf32(kd[1], p8.x, a1.x, p8.y, a1.y, x.x, x.y);
      x = cmulc(q2, make_float2(__shfl_sync(~0u, p2.x, s2), __shfl_sync(~0u, p2.y, s2)));
      mma_tf32(kd[2], p8.x, a1.x, p8.y, a1.y, x.x, x.y);
      x = cmulc(q3, make_float2(__shfl_sync(~0u, p128.x, s3), __shfl_sync(~0u, p128.y, s3)));
      mma_tf32(kd[3], p8.x, a1.x, p8.y, a1.y, x.x, x.y);
      x = cmulc(q4, p128);
      mma_tf32(kd[4], p8.x, a1.x, p8.y, a1.y, x.x, x.y);
    }
    char* kc = lb + L_KC + (warp & 3) * 2576;
#pragma unroll
    for (int e = 0; e < 2; e++) {
      const int row = g + e * 8;
      SM_F2(kc + 4 * (8 * row + 2 * cc)) = make_float2(kd[0][2 * e], kd[0][2 * e + 1]);
      SM_F2(kc + 4 * (128 + 8 * row + 2 * cc)) = make_float2(kd[1][2 * e], kd[1][2 * e + 1]);
      SM_F2(kc + 4 * (256 + 64 * (cc >> 1) + 4 * row + 2 * (cc & 1))) = make_float2(kd[2][2 * e], kd[2][2 * e + 1]);
      SM_F2(kc + 4 * (384 + 32 * cc + 2 * row)) = make_float2(kd[3][2 * e], kd[3][2 * e + 1]);
      SM_F32(kc + 4 * (512 + 32 * cc + row)) = kd[4][2 * e];
      SM_F32(kc + 4 * (528 + 32 * cc + row)) = kd[4][2 * e + 1];
    }
  }
  DBG_S(1);
  CH_SYNC();
  {
    const char* kc = lb + L_KC;
    auto kq = [&](int idx) {
      const char* q = kc + 4 * idx;
      return (*(const float*)q + *(const float*)(q + 2576)) + (*(const float*)(q + 5152) + *(const float*)(q + 7728));
    };
#pragma unroll
    for (int it = 0; it < 5; it++) {
      const int idx = n + 128 * it;
      float t = kq(idx);
      if ((it == 1 || it == 2) && n == 127) t -= kq(idx + 1);
      if (it == 4 && n == 0) { SM_F2(lb + L_KB) = make_float2(t, kq(640)); t = 0.f; }
      int off;
      if (it < 2) off = TP_0 + 2 * (272 - idx);
      else if (it == 2) {
        const int sel = n & 3, mu = 32 + (n >> 2);
        off = sel == 2 ? TP_W3B + 2 * (144 - mu) : (sel == 0 ? TP_W3A : sel == 1 ? TP_UA : TP_UB) + 2 * (80 - mu);
      } else if (it == 3) off = ((n & 1) ? TP_W3B : TP_W5) + 2 * (80 - (n >> 1));
      else off = ((n & 1) ? TP_W7 : TP_W9) + 2 * (80 - (n >> 1));
      const unsigned short hv = pack_bf16(t, 0.f);
      SM_U16(eb + E_TAP + off) = hv;
      SM_U16(eb + E_TAP + TP_COPY + off + 2) = hv;
    }
  }
  DBG_S(2);
  if (!lead && bid < 128) {
    uint32_t lw[9], lx[9], lg[9];
    const int row = bid * 16 + (warp - 8) * 2;
    ln_load(ar.u, ar.gate_w, row, lane, lw, lg);
    ln_load(ar.u, ar.gate_w, row + 1, lane, lx, lg);
    ln_row(row, lane, sc, lw, lg);
    ln_row(row + 1, lane, sc, lx, lg);
    asm volatile("bar.sync 5, 256;" ::: "memory");
  }
  if (lead) {
    mbar_wait(bars + B_U, pass & 1);
    if (pass > 0) mbar_wait(bars + B_COMB, (pass - 1) & 1);
    const uint32_t src = sb + xg_off(warp) + lane * 16;
    const int mych = g - (d0 & 4);
    char* dst = sm + l_off(mych) + (warp + 1) * 528 + cc * 4;
#pragma unroll
    for (int i = 0; i < 8; i++) {
      uint32_t r[4];
      ldsm4t(r, src + i * 512);
      if (mych >= 0 && mych < 4) {
#pragma unroll
        for (int k = 0; k < 4; k++) SM_U32(dst + i * 64 + k * 16) = r[k];
      }
    }
    __syncwarp();
    if (lane == 0) mbar_arrive(bars + B_U0);
    if (bid < 128 && tid == 0) {
      asm volatile("cp.async.bulk.prefetch.L2.global [%0], %1;" ::"l"(ar.w1 + (size_t)bid * 20736), "r"(41472) : "memory");
      asm volatile("cp.async.bulk.prefetch.L2.global [%0], %1;" ::"l"(ar.w2 + (size_t)bid * 20736), "r"(41472) : "memory");
    }
  }
  DBG_S(3);
  mbar_wait(bars + B_U0, pass & 1);
  DBG_S(4);
#pragma unroll 1
  for (int i = n - 1; i < 224; i += 128) {
    const char* ur = lb + ((i >> 5) + 1) * 528 + (i & 31) * 16;
    const uint4 w0 = *(const uint4*)(ur - ((i & 31) ? 16 : 32) + (i < 0 ? 16 : 0)), w1 = *(const uint4*)ur,
                w2 = *(const uint4*)(ur + ((i & 31) == 31 ? 32 : 16));
    const uint32_t wv[12] = {w0.x, w0.y, w0.z, w0.w, w1.x, w1.y, w1.z, w1.w, w2.x, w2.y, w2.z, w2.w};
    char* o = eb + 32 + 16 * i;
    SM_U4(o + E_UA) = make_uint4(wv[3], wv[4], wv[5], wv[6]);
    SM_U4(o + E_UB) = make_uint4(wv[1], wv[2], wv[3], wv[4]);
    float v[22], wa[16];
#pragma unroll
    for (int k = 1; k < 11; k++) { v[2 * k] = bf_lo(wv[k]); v[2 * k + 1] = bf_hi(wv[k]); }
#pragma unroll
    for (int k = 4; k < 16; k++) wa[k] = (v[k - 1] + v[k]) + v[k + 1];
    SM_U4(o + E_W3A) = make_uint4(pack_bf16(wa[8], wa[9]), pack_bf16(wa[10], wa[11]), pack_bf16(wa[12], wa[13]), pack_bf16(wa[14], wa[15]));
    SM_U4(o + E_W3B) = make_uint4(pack_bf16(wa[4], wa[5]), pack_bf16(wa[6], wa[7]), pack_bf16(wa[8], wa[9]), pack_bf16(wa[10], wa[11]));
    if (i < 192) {
#pragma unroll
      for (int k = 8; k < 16; k++) wa[k] += v[k - 2] + v[k + 2];
      SM_U4(o + E_W5) = make_uint4(pack_bf16(wa[8], wa[9]), pack_bf16(wa[10], wa[11]), pack_bf16(wa[12], wa[13]), pack_bf16(wa[14], wa[15]));
      if (i < 128) {
#pragma unroll
        for (int k = 8; k < 16; k++) wa[k] += v[k - 3] + v[k + 3];
        SM_U4(lb + L_W7 + 32 + 16 * i) =
            make_uint4(pack_bf16(wa[8], wa[9]), pack_bf16(wa[10], wa[11]), pack_bf16(wa[12], wa[13]), pack_bf16(wa[14], wa[15]));
#pragma unroll
        for (int k = 8; k < 16; k++) wa[k] += v[k - 4] + v[k + 4];
        SM_U4(o + E_W9) = make_uint4(pack_bf16(wa[8], wa[9]), pack_bf16(wa[10], wa[11]), pack_bf16(wa[12], wa[13]), pack_bf16(wa[14], wa[15]));
      }
    }
  }
  if (bid < 128 && tid == 480) {
    asm volatile("fence.acq_rel.gpu;" ::: "memory");
    atomicAdd(&sc.flags[256 + m], 1u);
  }
  __syncwarp();
  CH_SYNC();
  DBG_S(5);
  {
    const int role = (warp + ch) & 3;
    uint32_t ea = smem_u32(eb), za = smem_u32(lb);
    asm volatile("" : "+r"(ea), "+r"(za)::"memory");
    const uint32_t tp = ea + E_TAP + ((g & 1) ? TP_COPY + 2 : 0) - 2 * (g - 2 * cc);
    if (role < 2) {
      uint32_t ta[17][4];
      load_tquads<0, 17, TP_0 + 544>(ta, tp);
      float acc[8][4];
#pragma unroll
      for (int i = 0; i < 8; i++) { acc[i][0] = acc[i][1] = acc[i][2] = acc[i][3] = 0.f; }
      const uint32_t bpos = za + ((lane & 7) + 1) * 528 + role * 256 + (lane >> 3) * 16;
      const uint32_t bmid = role ? bpos : bpos - 16;
#pragma unroll
      for (int j2 = -16; j2 < 8; j2 += 2) {
        uint32_t b[4];
        ldsm4_free(b, (j2 < -8 ? bpos - 16 : j2 < 0 ? bmid : bpos) + 32 * j2);
#pragma unroll
        for (int hf = 0; hf < 2; hf++) {
#pragma unroll
          for (int i = 0; i < 8; i++) {
            const int k = i - j2 - hf;
            if (k >= 0 && k <= 16) mma_bf16(acc[i], ta[k][0], ta[k][1], ta[k][2], ta[k][3], b[2 * hf], b[2 * hf + 1]);
          }
        }
      }
      char* ya = lb + L_Y + 4 * (520 * cc + 128 * role + g);
#pragma unroll
      for (int i = 0; i < 8; i++) {
        SM_F32(ya + 64 * i) = acc[i][0]; SM_F32(ya + 64 * i + 1040) = acc[i][1];
        SM_F32(ya + 64 * i + 32) = acc[i][2]; SM_F32(ya + 64 * i + 1072) = acc[i][3];
      }
    } else if (role == 2) {
      p8_tiles<1, 11>(ea, za, lb, tp, lane);
    } else {
      p8_tiles<11, 16>(ea, za, lb, tp, lane);
      float acc[2][5][4];
#pragma unroll
      for (int i = 0; i < 10; i++) { acc[i / 5][i % 5][0] = acc[i / 5][i % 5][1] = acc[i / 5][i % 5][2] = acc[i / 5][i % 5][3] = 0.f; }
#pragma unroll
      for (int sg = 0; sg < 2; sg++) {
        uint32_t tq[5][4];
        if (sg == 0) load_tquads<4, 9, TP_W9 + 288>(tq, tp); else load_tquads<4, 9, TP_W7 + 288>(tq, tp);
        const uint32_t sa = (sg == 0 ? ea + E_W9 : za + L_W7 - 16) + 32 + (lane & 15) * 32 + (lane >> 4) * 16;
#pragma unroll
        for (int J = -1 + sg; J < 4; J++) {
          uint32_t b[4];
          ldsm4t_free(b, (J < 0 && (lane & 15) < 15) ? za : sa + J * 512);
#pragma unroll
          for (int k = 4; k < 9; k++) {
            const int I = J + k;
            if (I < 8) {
              mma_bf16(acc[0][I - 3], tq[k - 4][0], tq[k - 4][1], tq[k - 4][2], tq[k - 4][3], b[0], b[1]);
              mma_bf16(acc[1][I - 3], tq[k - 4][0], tq[k - 4][1], tq[k - 4][2], tq[k - 4][3], b[2], b[3]);
            }
          }
        }
      }
      char* a = lb + L_Y + 2 * L_YB + 4 * (16 * g + 2 * cc);
#pragma unroll
      for (int hh = 0; hh < 2; hh++) {
#pragma unroll
        for (int I = 3; I < 8; I++) {
          SM_F2(a + 32 * hh + 1040 * (I - 3)) = make_float2(acc[hh][I - 3][0], acc[hh][I - 3][1]);
          SM_F2(a + 32 * hh + 1040 * (I - 3) + 512) = make_float2(acc[hh][I - 3][2], acc[hh][I - 3][3]);
        }
      }
    }
  }
  __syncwarp();
  if (lane == 0) {
    mbar_arrive(bars + B_CONV);
    if (!lead) {
      const int iw = warp - 8;
      mbar_wait(bars + B_CONV, pass & 1);
      HFENCE();
      if (bid >= 128) {
        if (pass < 3) {
          mbar_expect_tx(bars + B_U, 4096);
          tma2d(sb + xg_off(iw), tm.x, (d0 + 4) & ~7, iw * 256, bars + B_U);
        }
      } else if (iw < 6) {
        mbar_expect_tx(bars + B_FULL + 8 * iw, STAGE_BYTES);
        tma3d(sb + OFF_ST + iw * STAGE_BYTES, tm.w1, 0, iw * 64, f * 18, bars + B_FULL + 8 * iw);
      } else {
        wait_flag(&sc.flags[256 + m], 8);
        mbar_expect_tx(bars + B_X + 8 * (iw - 6), 16384);
        tma2d(sb + (iw - 6) * 16384, tm.xn, (iw - 6) * 64, m * 128, bars + B_X + 8 * (iw - 6));
      }
    }
  }
  __syncwarp();
  CH_SYNC();
  DBG_S(6);
  uint32_t pnext[8];
#pragma unroll
  for (int i = 0; i < 8; i++) pnext[i] = 0;
  if (bid >= 128 && pass < 3) load_params(pnext, ar, d0 + 4 + ch, n);
  {
    const float4 kb = SM_F4(lb + L_KB);
    const uint32_t dk = pack_bf16(kb.z, kb.z);
#pragma unroll
    for (int k = 0; k < 4; k++) {
      const int t0 = n * 4 + 512 * k;
      char* ya = lb + L_Y + 4 * (t0 + 4 * (t0 >> 8));
      float4 y = SM_F4(ya);
      if (k > 0 || t0 >= 128) { const float4 b = SM_F4(ya + L_YB); y.x += b.x; y.y += b.y; y.z += b.z; y.w += b.w; }
      if (k > 1 || (k == 1 && t0 >= 768)) {
        const float4 b = SM_F4(ya + 2 * L_YB - 3120);
        y.x += b.x; y.y += b.y; y.z += b.z; y.w += b.w;
        if (k > 1 || t0 >= 1020) {
          const char* wp = lb + L_W7 + 32 + 2 * (t0 - 1026);
          const uint32_t wl = *(const uint32_t*)wp, wm = *(const uint32_t*)(wp + 4), wh = *(const uint32_t*)(wp + 8);
          y.x = fmaf(kb.x, bf_hi(wl), y.x); y.y = fmaf(kb.x, bf_lo(wm), y.y);
          y.z = fmaf(kb.x, bf_hi(wm), y.z); y.w = fmaf(kb.x, bf_lo(wh), y.w);
          if (k == 3 && n == 127) {
            const uint2 u03 = SM_U2(lb + 528);
            float pre = bf_lo(u03.x);
            y.x = fmaf(kb.y, pre, y.x); pre += bf_hi(u03.x);
            y.y = fmaf(kb.y, pre, y.y); pre += bf_lo(u03.y);
            y.z = fmaf(kb.y, pre, y.z); pre += bf_hi(u03.y);
            y.w = fmaf(kb.y, pre, y.w);
          }
        }
      }
      const uint2 uu = SM_U2(lb + ((t0 >> 8) + 1) * 528 + (t0 & 255) * 2);
      uint2 o;
      o.x = bf2_add(pack_bf16(y.x, y.y), bf2_mul(uu.x, dk));
      o.y = bf2_add(pack_bf16(y.z, y.w), bf2_mul(uu.y, dk));
      *reinterpret_cast<uint2*>(sc.aT + (size_t)(d0 + ch) * L_SEQ + t0) = o;
    }
  }
  __syncwarp();
  if (lane == 0) mbar_arrive(bars + B_COMB);
  CH_SYNC();
  DBG_S(7);
  return pack_params(pnext);
}

__global__ void __cluster_dims__(2, 1, 1) __launch_bounds__(512, 1)
fused_kernel(const __grid_constant__ CUtensorMap tm_x, const __grid_constant__ CUtensorMap tm_w1,
             const __grid_constant__ CUtensorMap tm_w2, const __grid_constant__ CUtensorMap tm_aT,
             const __grid_constant__ CUtensorMap tm_xn, const __grid_constant__ CUtensorMap tm_out,
             const __grid_constant__ CUtensorMap tm_a8,
             const __grid_constant__ Args ar, const __grid_constant__ Scratch sc) {
  extern __shared__ __align__(1024) char smem_raw[];
  DBG_G(28);
  const uint32_t sb = (smem_u32(smem_raw) + 1023) & ~1023u;
  char* sm = smem_raw + (sb - smem_u32(smem_raw));
  const uint32_t bars = sb + OFF_BAR;
  const int tid = threadIdx.x, lane = tid & 31;
  const int warp = __shfl_sync(0xffffffffu, tid >> 5, 0), wg = warp >> 2;
  const int bid = blockIdx.x;
  const int m = bid >> 3, f = bid & 7, rank = f & 1, pr = f >> 1;

  const int dbase = bid < 128 ? bid * 4 : 512 + (bid - 128) * 16;
  uint32_t praw[8];
  load_params(praw, ar, dbase + wg, tid & 127);

  if (lane == 0) {
    if (warp == 8) {
#pragma unroll
      for (int i = 0; i < B_EMPTY / 8; i++) mbar_init(bars + i * 8, 1);
      asm volatile("fence.mbarrier_init.release.cluster;" ::: "memory");
#pragma unroll
      for (int i = 0; i < 4; i++) mbar_expect_tx(bars + B_RB + 8 * i, 16384);
    } else if (warp == 9) {
#pragma unroll
      for (int i = B_EMPTY / 8; i < NBARS; i++) mbar_init(bars + i * 8, 8);
      mbar_init(bars + B_CONV, 16);
      mbar_init(bars + B_COMB, 16);
      asm volatile("fence.mbarrier_init.release.cluster;" ::: "memory");
    } else if (warp == 10) {
      asm volatile("prefetch.tensormap [%0];" ::"l"(&tm_x) : "memory");
    } else if (warp == 11) {
      *reinterpret_cast<Args*>(sm + OFF_ARGS) = ar;
      *reinterpret_cast<Scratch*>(sm + OFF_ARGS + 128) = sc;
    }
  }
  __syncthreads();
  asm volatile("barrier.cluster.arrive.relaxed.aligned;" ::: "memory");

  {
    Maps tm;
    tm.x = &tm_x; tm.w1 = &tm_w1; tm.xn = &tm_xn;
    const int npass = bid < 128 ? 1 : 4;
    if (lane == 0 && (warp & 1) == 0) {
      mbar_expect_tx(bars + B_U, 4096);
      tma2d(sb + xg_off(warp >> 1), &tm_x, dbase & ~7, (warp >> 1) * 256, bars + B_U);
    }
    {
      char* eb = sm + e_off(wg);
      const int n = tid & 127;
      const uint4 z = make_uint4(0, 0, 0, 0);
      SM_U4(eb + E_TAP + n * 16) = z;
      if (n < 104) SM_U4(eb + E_TAP + 2048 + n * 16) = z;
      else if (n == 104) SM_U4(eb + E_W9) = z;
      if (n < 33) SM_U4(sm + l_off(wg) + n * 16) = z;
    }
    uint4 pv = pack_params(praw);
#pragma unroll 1
    for (int pass = 0; pass < npass; pass++)
      pv = ssm_pass(tm, sm, dbase + pass * 4, pass, pv
      );
  }
  __syncthreads();
  if (bid >= 128) {
    if (tid == 0) {
      asm volatile("fence.acq_rel.gpu;" ::: "memory");
      atomicAdd(&sc.flags[304], 1u);
    }
    __syncwarp();
    asm volatile("barrier.cluster.wait.acquire.aligned;" ::: "memory");
    return;
  }

  const uint32_t rdelta = mapa(sb, rank ^ 1) - sb;
  if (wg >= 2) {
    asm volatile("setmaxnreg.dec.sync.aligned.u32 24;");
    asm volatile("barrier.cluster.wait.acquire.aligned;" ::: "memory");
    const int pw = warp - 8;
    if (lane == 0) {
      if (pw < 2) {
        int slot = pw, par = 0;
#pragma unroll 1
        for (int it = 6 + pw; it < 54; it += 2) {
          const int ch = it / 9, s = it - ch * 9;
          const uint32_t fb = bars + B_FULL + 8 * slot;
          mbar_wait(bars + B_EMPTY + 8 * slot, par);
          mbar_expect_tx(fb, STAGE_BYTES);
          tma3d(sb + OFF_ST + slot * STAGE_BYTES, &tm_w1, 0, s * 64, f * 18 + ch * 3, fb);
          slot += 2;
          if (slot >= 6) { slot -= 6; par ^= 1; }
        }
#pragma unroll 1
        for (int pos = 0; pos < 9; pos++) {
          const int chunk = chunk_of(pos, pr, rank);
#pragma unroll 1
          for (slot = pw; slot < 6; slot += 2) {
            const uint32_t fb = bars + B_FULL + 8 * slot;
            mbar_wait(bars + B_EMPTY + 8 * slot, par);
            mbar_expect_tx(fb, STAGE_BYTES);
            tma2d(sb + OFF_ST + slot * STAGE_BYTES, &tm_w2, chunk * 64, f * 576 + slot * 96, fb);
          }
          par ^= 1;
        }
        if (pw == 0) {
          wait_flag(&sc.flags[288 + f * 2], 16);
          mbar_wait(bars + B_EMPTY, par);
          mbar_wait(bars + B_EMPTY + 8, par);
          mbar_expect_tx(bars + B_FULL, 16384);
          tma2d(sb + OFF_ST, &tm_aT, m * 128, f * 64, bars + B_FULL);
          tma2d(sb + OFF_ST + 8192, &tm_aT, m * 128 + 64, f * 64, bars + B_FULL);
          if (atomicAdd(&sc.flags[289 + f * 2], 1u) == 15) { sc.flags[288 + f * 2] = 0; sc.flags[289 + f * 2] = 0; }
        }
      } else if (pw == 2) {
        mbar_wait(bars + B_P1R, 0);
#pragma unroll 1
        for (int k = 0; k < 4; k++) {
          mbar_wait(bars + B_TS + 8 * k, 0);
          HFENCE();
          bulk_s2peer(sb + k * 16384 + rdelta, sb + OFF_STG + k * 16384, 16384, bars + B_RB + 8 * k + rdelta);
        }
#pragma unroll 1
        for (int k = 0; k < 4; k++) mbar_wait(bars + B_RB + 8 * k, 0);
        mbar_arrive_remote(bars + B_FIN + rdelta);
        mbar_wait(bars + B_FIN, 0);
      } else if (pw == 3) {
        mbar_wait(bars + B_TS8, 0);
        HFENCE();
        bulk_s2g_release(sc.slots8 + (size_t)(m * 8 + f) * 4096, sb + OFF_C8, 16384);
#pragma unroll 1
        for (int i = 0; i < 8; i++) atomicAdd(&sc.flags[m * 16 + 8 + i], 1u);
#pragma unroll 1
        for (int k = 0; k < 2; k++) {
          const int chunk = 2 * ((pr + k + 1) & 3) + rank;
          mbar_wait(bars + B_TR + 8 * k, 0);
          HFENCE();
          bulk_s2g_release(sc.slots + (size_t)((m * 8 + chunk) * 3 + k) * 4096, sb + k * 16384, 16384);
          atomicAdd(&sc.flags[320 + (m * 8 + chunk) * 4 + k], 1u);
          DBG_H(16 + k);
          if (k == 0) {
            mbar_expect_tx(bars + B_OWN, 49152);
            wait_flag(&sc.flags[m * 16 + 8 + f], 8);
            sc.flags[m * 16 + 8 + f] = 0;
#pragma unroll 1
            for (int i = 0; i < 8; i++)
              bulk_g2s(sb + OFF_C8 + i * 2048, sc.slots8 + (size_t)(m * 8 + i) * 4096 + f * 512, 2048, bars + B_OWN);
          }
        }
#pragma unroll 1
        for (int j = 0; j < 2; j++) {
          unsigned int* fl = &sc.flags[320 + (m * 8 + f) * 4 + j];
          wait_flag(fl, 1);
          *fl = 0;
          bulk_g2s(sb + j * 16384, sc.slots + (size_t)((m * 8 + f) * 3 + j) * 4096, 16384, bars + B_OWN);
        }
        if (f == 0) sc.flags[256 + m] = 0;
        DBG_H(19);
      } else if (pw == 4) {
        asm volatile("fence.acq_rel.gpu;" ::: "memory");
        atomicAdd(&sc.flags[288 + (bid >> 4) * 2], 1u);
        mbar_wait(bars + B_TR + 8, 0);
        wait_flag(&sc.flags[304], 4);
        mbar_expect_tx(bars + B_A8, 2048);
        tma2d(sb + OFF_A8, &tm_a8, m * 128, 512 + f * 8, bars + B_A8);
        if (atomicAdd(&sc.flags[305], 1u) == 127) { sc.flags[304] = 0; sc.flags[305] = 0; }
      } else {
        HFENCE();
#pragma unroll 1
        for (int kb = pw - 3; kb < 9; kb += 3) {
          mbar_expect_tx(bars + B_X + 8 * kb, kb == 8 ? 16384 + 2304 : 16384);
          tma2d(sb + kb * 16384, &tm_xn, kb * 64, m * 128, bars + B_X + 8 * kb);
          if (kb == 8) {
            bulk_g2s(sb + OFF_B1, ar.b1 + f * 576, 1152, bars + B_X + 64);
            bulk_g2s(sb + OFF_B2, ar.b2, 1152, bars + B_X + 64);
          }
        }
        if (pw == 6) {
          const int chunk = 2 * ((pr + 3) & 3) + rank;
          mbar_wait(bars + B_TR + 16, 0);
          HFENCE();
          bulk_s2g_release(sc.slots + (size_t)((m * 8 + chunk) * 3 + 2) * 4096, sb + 32768, 16384);
          atomicAdd(&sc.flags[320 + (m * 8 + chunk) * 4 + 2], 1u);
          DBG_H(18);
          unsigned int* fl = &sc.flags[320 + (m * 8 + f) * 4 + 2];
          mbar_expect_tx(bars + B_OWN2, 16384);
          wait_flag(fl, 1);
          *fl = 0;
          bulk_g2s(sb + 32768, sc.slots + (size_t)((m * 8 + f) * 3 + 2) * 4096, 16384, bars + B_OWN2);
        }
      }
    }
  } else {
    asm volatile("setmaxnreg.inc.sync.aligned.u32 232;");
    const int wi = warp & 3;
    DBG_T(0);
    MlpCtx c;
    c.bars = bars; c.lane = lane;
    c.dA = (((sb + wg * 8192) & 0x3FFFF) >> 4) | (1u << 16);
    c.dB = ((sb + OFF_ST) & 0x3FFFF) >> 4;

    uint32_t h[144];
    float acc2a[32], acc2b[32];
    {
      float accA[48], accB[48];
#pragma unroll
      for (int i = 0; i < 48; i++) { accA[i] = 0.f; accB[i] = 0.f; }
#pragma unroll
      for (int i = 0; i < 144; i++) h[i] = 0;
      uint32_t baddr = sb + OFF_B1 + (lane & 3) * 4 - 192;
#pragma unroll 1
      for (int j = 0; j < 3; j++) {
        DBG_T(11 + 2 * j);
        p1_chunk<0>(c, j, baddr, accA, accB, h);
        baddr += 192;
        DBG_T(10 + 2 * j);
        p1_chunk<9>(c, j, baddr, accB, accA, h);
        baddr += 192;
      }
      DBG_T(2);
      p2_mma<0>(c, 1, acc2a, h);
      wg_wait<1>();
      stage_release(c, 5);
      fence_regs(accB);
      asm volatile("barrier.cluster.wait.acquire.aligned;" ::: "memory");
      if (lane == 0) { mbar_arrive(bars + B_P1L); mbar_arrive_remote(bars + B_P1R + rdelta); }
      p2_mma<1>(c, 1, acc2a, h);
      gelu_part<0>(baddr, accB); gelu_part<1>(baddr, accB);
      wg_wait<1>(); stage_release(c, 0);
      p2_mma<2>(c, 1, acc2a, h);
      gelu_part<2>(baddr, accB); gelu_part<3>(baddr, accB);
      wg_wait<1>(); stage_release(c, 1);
      p2_mma<3>(c, 1, acc2a, h);
      gelu_part<4>(baddr, accB);
      wg_wait<1>(); stage_release(c, 2);
      p2_mma<4>(c, 1, acc2a, h);
      gelu_part<5>(baddr, accB);
#pragma unroll
      for (int i = 0; i < 24; i++) h[120 + i] = __float_as_uint(accB[(i >> 2) * 8 + (i & 3)]);
      wg_wait<1>(); stage_release(c, 3);
      p2_mma<5>(c, 1, acc2a, h);
      wg_wait<1>(); stage_release(c, 4);
    }
    const uint32_t lbuf = sb + warp * 2048 + lane * 16;
    mbar_wait(bars + B_P1L, 0);
#pragma unroll 1
    for (int pos = 0; pos < 8; pos++) {
      const bool recv = (0x68 >> pos) & 1;
      const int k = recv ? (pos - 2) >> 1 : (pos + 1) >> 1;
      const int ks = k > 3 ? 3 : k;
      const uint32_t addr = lbuf + ks * 16384 + (recv ? 0 : OFF_STG);
      const uint32_t sig = bars + (recv ? B_TR + 8 * k : pos == 1 ? B_TS8 : B_TS + 8 * ks);
      if (recv) mbar_wait(bars + B_RB + k * 8, 0);
      wg_wait<0>(); stage_release(c, 5);
      fence_regs(acc2a);
      DBG_T(20 + pos);
      if (recv) {
#pragma unroll
        for (int i = 0; i < 4; i++) {
          const float4 r = lds128f(addr + i * 512);
          const uint32_t w0 = __float_as_uint(r.x), w1 = __float_as_uint(r.y), w2 = __float_as_uint(r.z), w3 = __float_as_uint(r.w);
          acc2a[8 * i + 0] += bf_lo(w0); acc2a[8 * i + 1] += bf_hi(w0); acc2a[8 * i + 2] += bf_lo(w1); acc2a[8 * i + 3] += bf_hi(w1);
          acc2a[8 * i + 4] += bf_lo(w2); acc2a[8 * i + 5] += bf_hi(w2); acc2a[8 * i + 6] += bf_lo(w3); acc2a[8 * i + 7] += bf_hi(w3);
        }
      }
      if (pos == 1) {
        const uint32_t a8 = sb + OFF_C8 + warp * 256 + lane * 8;
#pragma unroll
        for (int q = 0; q < 8; q++)
          asm volatile("st.shared.v2.u32 [%0], {%1,%2};" ::"r"(a8 + q * 2048), "r"(pack_bf16(acc2a[4 * q], acc2a[4 * q + 1])),
                       "r"(pack_bf16(acc2a[4 * q + 2], acc2a[4 * q + 3])) : "memory");
      } else {
#pragma unroll
        for (int i = 0; i < 4; i++)
          sts128(addr + i * 512, pack_bf16(acc2a[8 * i], acc2a[8 * i + 1]), pack_bf16(acc2a[8 * i + 2], acc2a[8 * i + 3]),
                 pack_bf16(acc2a[8 * i + 4], acc2a[8 * i + 5]), pack_bf16(acc2a[8 * i + 6], acc2a[8 * i + 7]));
      }
      const uint32_t par = pos & 1;
      p2_mma<0>(c, par, acc2a, h);
      __syncwarp();
      if (lane == 0) mbar_arrive(sig);
      p2_mma<1>(c, par, acc2a, h);
      wg_wait<1>(); stage_release(c, 0);
      p2_mma<2>(c, par, acc2a, h);
      wg_wait<1>(); stage_release(c, 1);
      p2_mma<3>(c, par, acc2a, h);
      wg_wait<1>(); stage_release(c, 2);
      p2_mma<4>(c, par, acc2a, h);
      wg_wait<1>(); stage_release(c, 3);
      p2_mma<5>(c, par, acc2a, h);
      wg_wait<1>(); stage_release(c, 4);
    }
    DBG_T(3);
    {
      const int g = lane >> 2, cc = lane & 3;
      const int t0 = m * 128 + warp * 16 + g;
      const uint2 ga = __ldcg(&sc.gate[t0]), gb = __ldcg(&sc.gate[t0 + 8]);
#pragma unroll
      for (int i = 0; i < 32; i++) acc2b[i] = 0.f;
      auto add_tile = [&](int k) {
#pragma unroll
        for (int i = 0; i < 4; i++) {
          float4 r = lds128f(lbuf + k * 16384 + i * 512);
          const uint32_t w0 = __float_as_uint(r.x), w1 = __float_as_uint(r.y), w2 = __float_as_uint(r.z), w3 = __float_as_uint(r.w);
          acc2b[8 * i + 0] += bf_lo(w0); acc2b[8 * i + 1] += bf_hi(w0); acc2b[8 * i + 2] += bf_lo(w1); acc2b[8 * i + 3] += bf_hi(w1);
          acc2b[8 * i + 4] += bf_lo(w2); acc2b[8 * i + 5] += bf_hi(w2); acc2b[8 * i + 6] += bf_lo(w3); acc2b[8 * i + 7] += bf_hi(w3);
        }
      };
      mbar_wait(bars + B_OWN, 0);
      add_tile(0);
      add_tile(1);
      float c8[4] = {0.f, 0.f, 0.f, 0.f};
#pragma unroll
      for (int i = 0; i < 8; i++) {
        uint32_t w0, w1;
        asm volatile("ld.shared.v2.u32 {%0,%1}, [%2];" : "=r"(w0), "=r"(w1) : "r"(sb + OFF_C8 + i * 2048 + warp * 256 + lane * 8));
        c8[0] += bf_lo(w0); c8[1] += bf_hi(w0); c8[2] += bf_lo(w1); c8[3] += bf_hi(w1);
      }
      mbar_wait(bars + B_RB + 24, 0);
      add_tile(3);
      mbar_wait(bars + B_OWN2, 0);
      DBG_T(8);
      add_tile(2);
      DBG_T(9);
      mbar_wait(bars + B_FULL, 0);
      wg_wait<0>();
      fence_regs(acc2a);
      DBG_T(4);
#pragma unroll
      for (int jj = 0; jj < 4; jj++) {
        uint32_t a[4];
        {
          const int dl = 8 * (2 * jj + (lane >> 4)) + (lane & 7);
          const int chk = 2 * wi + ((lane >> 3) & 1);
          ldsm4t(a, sb + OFF_ST + wg * 8192 + dl * 128 + ((chk ^ (dl & 7)) << 4));
        }
        uint32_t o[4];
#pragma unroll
        for (int e = 0; e < 2; e++) {
          const int q = 2 * jj + e;
          uint32_t bb = lds32(sb + OFF_B2 + (f * 64 + q * 8 + cc * 2) * 2);
          uint32_t v0 = bf2_add(pack_bf16(acc2a[4 * q] + acc2b[4 * q], acc2a[4 * q + 1] + acc2b[4 * q + 1]), bb);
          uint32_t v1 = bf2_add(pack_bf16(acc2a[4 * q + 2] + acc2b[4 * q + 2], acc2a[4 * q + 3] + acc2b[4 * q + 3]), bb);
          o[2 * e] = bf2_add(bf2_mul(ga.x, a[2 * e]), bf2_mul(ga.y, v0));
          o[2 * e + 1] = bf2_add(bf2_mul(gb.x, a[2 * e + 1]), bf2_mul(gb.y, v1));
        }
        {
          const int row = (lane & 7) + ((lane >> 3) & 1) * 8;
          const uint32_t addr = sb + 49152 + warp * 2048 + row * 128 + (((2 * jj + (lane >> 4)) ^ (row & 7)) << 4);
          asm volatile("stmatrix.sync.aligned.m8n8.x4.shared.b16 [%0], {%1,%2,%3,%4};"
                       ::"r"(addr), "r"(o[0]), "r"(o[1]), "r"(o[2]), "r"(o[3]) : "memory");
        }
      }
      asm volatile("fence.proxy.async.shared::cta;" ::: "memory");
      __syncwarp();
      if (lane == 0) {
        asm volatile("cp.async.bulk.tensor.2d.global.shared::cta.bulk_group [%0, {%2, %3}], [%1];\n"
                     "cp.async.bulk.commit_group;"
                     ::"l"(&tm_out), "r"(sb + 49152 + warp * 2048), "r"(f * 64), "r"(m * 128 + warp * 16) : "memory");
      }
      __syncwarp();
      mbar_wait(bars + B_A8, 0);
      {
        __nv_bfloat16* op = ar.out + (size_t)t0 * D_MOD + cc * 2 + 512 + f * 8;
        uint32_t a0, a1;
        const uint32_t addr = sb + OFF_A8 + (lane & 7) * 256 + (warp * 2 + ((lane >> 3) & 1)) * 16;
        asm volatile("ldmatrix.sync.aligned.m8n8.x2.trans.shared.b16 {%0,%1}, [%2];" : "=r"(a0), "=r"(a1) : "r"(addr));
        const uint32_t bb = lds32(sb + OFF_B2 + (512 + f * 8 + cc * 2) * 2);
        const uint32_t v0 = bf2_add(pack_bf16(c8[0], c8[1]), bb), v1 = bf2_add(pack_bf16(c8[2], c8[3]), bb);
        *reinterpret_cast<uint32_t*>(op) = bf2_add(bf2_mul(ga.x, a0), bf2_mul(ga.y, v0));
        *reinterpret_cast<uint32_t*>(op + 8 * D_MOD) = bf2_add(bf2_mul(gb.x, a1), bf2_mul(gb.y, v1));
      }
      if (lane == 0) asm volatile("cp.async.bulk.wait_group.read 0;" ::: "memory");
      DBG_T(5);
      DBG_G(29);
    }
  }
}

typedef CUresult (*EncodeTiledFn)(CUtensorMap*, CUtensorMapDataType, cuuint32_t, void*, const cuuint64_t*,
                                  const cuuint64_t*, const cuuint32_t*, const cuuint32_t*, CUtensorMapInterleave,
                                  CUtensorMapSwizzle, CUtensorMapL2promotion, CUtensorMapFloatOOBfill);

static void make_map(EncodeTiledFn enc, CUtensorMap* tm, const void* base, uint64_t inner, uint64_t outer, uint32_t binner,
                     uint32_t bouter, CUtensorMapSwizzle swz) {
  cuuint64_t gd[2] = {inner, outer};
  cuuint64_t gs[1] = {inner * 2};
  cuuint32_t bd[2] = {binner, bouter};
  cuuint32_t es[2] = {1, 1};
  enc(tm, CU_TENSOR_MAP_DATA_TYPE_BFLOAT16, 2, const_cast<void*>(base), gd, gs, bd, es, CU_TENSOR_MAP_INTERLEAVE_NONE, swz,
      CU_TENSOR_MAP_L2_PROMOTION_L2_128B, CU_TENSOR_MAP_FLOAT_OOB_FILL_NONE);
}

extern "C" void kernel_launch(void* const* d_in, const int* in_sizes, int n_in, void* d_out, int out_size) {
  typedef const __nv_bfloat16* BP;
  Args ar;
  ar.u = (BP)d_in[0]; ar.Are = (BP)d_in[1]; ar.Aim = (BP)d_in[2]; ar.Bre = (BP)d_in[3]; ar.Bim = (BP)d_in[4];
  ar.Cre = (BP)d_in[5]; ar.Cim = (BP)d_in[6]; ar.logdt = (BP)d_in[7]; ar.Dskip = (BP)d_in[8];
  ar.w1 = (BP)d_in[10]; ar.b1 = (BP)d_in[11]; ar.w2 = (BP)d_in[12]; ar.b2 = (BP)d_in[13]; ar.gate_w = (BP)d_in[14];
  ar.out = (__nv_bfloat16*)d_out;

  static EncodeTiledFn enc = nullptr;
  static Scratch sc;
  if (!enc) {
    cudaDriverEntryPointQueryResult qr;
    cudaGetDriverEntryPoint("cuTensorMapEncodeTiled", (void**)&enc, cudaEnableDefault, &qr);
    cudaGetSymbolAddress((void**)&sc.aT, g_aT);
    cudaGetSymbolAddress((void**)&sc.xn, g_xn);
    cudaGetSymbolAddress((void**)&sc.gate, g_gate);
    cudaGetSymbolAddress((void**)&sc.slots, g_slots);
    cudaGetSymbolAddress((void**)&sc.slots8, g_slots8);
    cudaGetSymbolAddress((void**)&sc.flags, g_flags);
    sc.dbg = nullptr;
    cudaFuncSetAttribute(fused_kernel, cudaFuncAttributeMaxDynamicSharedMemorySize, SMEM_BYTES);
  }
  CUtensorMap tm_x, tm_w1, tm_w2, tm_aT, tm_xn, tm_out, tm_a8;
  make_map(enc, &tm_a8, sc.aT, L_SEQ, D_MOD, 128, 8, CU_TENSOR_MAP_SWIZZLE_NONE);
  make_map(enc, &tm_x, ar.u, D_MOD, L_SEQ, 8, 256, CU_TENSOR_MAP_SWIZZLE_NONE);
  make_map(enc, &tm_w2, ar.w2, D_MOD, F_HID, 64, 96, CU_TENSOR_MAP_SWIZZLE_128B);
  make_map(enc, &tm_aT, sc.aT, L_SEQ, D_MOD, 64, 64, CU_TENSOR_MAP_SWIZZLE_128B);
  make_map(enc, &tm_xn, sc.xn, D_MOD, L_SEQ, 64, 128, CU_TENSOR_MAP_SWIZZLE_128B);
  make_map(enc, &tm_out, d_out, D_MOD, L_SEQ, 64, 16, CU_TENSOR_MAP_SWIZZLE_128B);
  {
    cuuint64_t gd[3] = {32, D_MOD, F_HID / 32};
    cuuint64_t gs[2] = {F_HID * 2, 64};
    cuuint32_t bd[3] = {32, 64, 3};
    cuuint32_t es[3] = {1, 1, 1};
    enc(&tm_w1, CU_TENSOR_MAP_DATA_TYPE_BFLOAT16, 3, (void*)ar.w1, gd, gs, bd, es, CU_TENSOR_MAP_INTERLEAVE_NONE,
        CU_TENSOR_MAP_SWIZZLE_64B, CU_TENSOR_MAP_L2_PROMOTION_L2_128B, CU_TENSOR_MAP_FLOAT_OOB_FILL_NONE);
  }
  fused_kernel<<<132, 512, SMEM_BYTES, cudaStreamPerThread>>>(tm_x, tm_w1, tm_w2, tm_aT, tm_xn, tm_out, tm_a8, ar, sc);
}
```

```cpp
#include <cuda_runtime.h>
#include <cuda_bf16.h>
#include <cuda.h>
#include <stdint.h>

#define HFENCE() asm volatile("fence.proxy.async.shared::cta;" ::: "memory")
#define L_SEQ 2048
#define D_MOD 576
#define F_HID 4608
#define N_ST 128

__device__ __align__(1024) __nv_bfloat16 g_aT[D_MOD * L_SEQ];
__device__ __align__(1024) __nv_bfloat16 g_xn[L_SEQ * D_MOD];
__device__ __align__(1024) uint32_t g_slots[16 * 8 * 3 * 4096];
__device__ __align__(1024) uint32_t g_slots8[16 * 8 * 4096];
__device__ uint2 g_gate[L_SEQ];
__device__ unsigned int g_flags[832];
struct Scratch {
  __nv_bfloat16* aT; __nv_bfloat16* xn; uint2* gate; uint32_t* slots; uint32_t* slots8; unsigned int* flags;
  long long* dbg;
};
#define DBG_T(i)
#define DBG_S(i)
#define DBG_H(i)
#define DBG_G(i)

__device__ __forceinline__ uint32_t smem_u32(const void* p) { return (uint32_t)__cvta_generic_to_shared(p); }
__device__ __forceinline__ void mbar_init(uint32_t bar, int cnt) {
  asm volatile("mbarrier.init.shared::cta.b64 [%0], %1;" ::"r"(bar), "r"(cnt));
}
__device__ __forceinline__ void mbar_expect_tx(uint32_t bar, uint32_t bytes) {
  asm volatile("mbarrier.arrive.expect_tx.shared::cta.b64 _, [%0], %1;" ::"r"(bar), "r"(bytes) : "memory");
}
__device__ __forceinline__ void mbar_arrive(uint32_t bar) {
  asm volatile("mbarrier.arrive.shared::cta.b64 _, [%0];" ::"r"(bar) : "memory");
}
__device__ __forceinline__ void mbar_arrive_remote(uint32_t remote_bar) {
  asm volatile("mbarrier.arrive.relaxed.cluster.shared::cluster.b64 _, [%0];" ::"r"(remote_bar) : "memory");
}
__device__ __forceinline__ void mbar_wait(uint32_t bar, uint32_t parity) {
  asm volatile(
      "{\n.reg .pred p;\n.reg .u32 n;\nmov.u32 n, 0;\n"
      "W_%=:\nmbarrier.try_wait.parity.shared::cta.b64 p, [%0], %1;\n@p bra D_%=;\n"
      "add.u32 n, n, 1;\nsetp.lt.u32 p, n, 400000;\n@p bra W_%=;\ntrap;\nD_%=:\n}"
      ::"r"(bar), "r"(parity) : "memory");
}
__device__ __forceinline__ void tma2d(uint32_t dst, const CUtensorMap* tm, int c0, int c1, uint32_t bar) {
  asm volatile("cp.async.bulk.tensor.2d.shared::cluster.global.mbarrier::complete_tx::bytes [%0], [%1, {%3, %4}], [%2];"
               ::"r"(dst), "l"(tm), "r"(bar), "r"(c0), "r"(c1) : "memory");
}
__device__ __forceinline__ void wait_flag(unsigned int* flag, unsigned int target) {
  asm volatile(
      "{\n.reg .pred p;\n.reg .u32 n, v;\nmov.u32 n, 0;\n"
      "W_%=:\nld.acquire.gpu.global.u32 v, [%0];\nsetp.ge.u32 p, v, %1;\n@p bra D_%=;\n"
      "nanosleep.u32 32;\nadd.u32 n, n, 1;\nsetp.lt.u32 p, n, 4000000;\n@p bra W_%=;\ntrap;\nD_%=:\n}"
      ::"l"(flag), "r"(target) : "memory");
}
__device__ __forceinline__ void bulk_g2s(uint32_t dst, const void* src, uint32_t bytes, uint32_t bar) {
  asm volatile("cp.async.bulk.shared::cluster.global.mbarrier::complete_tx::bytes [%0], [%1], %2, [%3];"
               ::"r"(dst), "l"(src), "r"(bytes), "r"(bar) : "memory");
}
__device__ __forceinline__ void tma3d(uint32_t dst, const CUtensorMap* tm, int c0, int c1, int c2, uint32_t bar) {
  asm volatile("cp.async.bulk.tensor.3d.shared::cluster.global.mbarrier::complete_tx::bytes [%0], [%1, {%3, %4, %5}], [%2];"
               ::"r"(dst), "l"(tm), "r"(bar), "r"(c0), "r"(c1), "r"(c2) : "memory");
}
__device__ __forceinline__ uint32_t mapa(uint32_t addr, uint32_t rank) {
  uint32_t r;
  asm("mapa.shared::cluster.u32 %0, %1, %2;" : "=r"(r) : "r"(addr), "r"(rank));
  return r;
}
__device__ __forceinline__ float4 lds128f(uint32_t addr) {
  float4 v;
  asm volatile("ld.shared.v4.f32 {%0,%1,%2,%3}, [%4];" : "=f"(v.x), "=f"(v.y), "=f"(v.z), "=f"(v.w) : "r"(addr));
  return v;
}
__device__ __forceinline__ uint32_t lds32(uint32_t addr) {
  uint32_t v;
  asm volatile("ld.shared.u32 %0, [%1];" : "=r"(v) : "r"(addr));
  return v;
}
__device__ __forceinline__ void sts128(uint32_t addr, uint32_t a, uint32_t b, uint32_t c, uint32_t d) {
  asm volatile("st.shared.v4.u32 [%0], {%1,%2,%3,%4};" ::"r"(addr), "r"(a), "r"(b), "r"(c), "r"(d) : "memory");
}
#define WG_FENCE() asm volatile("wgmma.fence.sync.aligned;" ::: "memory")
#define WG_COMMIT() asm volatile("wgmma.commit_group.sync.aligned;" ::: "memory")
template <int n> __device__ __forceinline__ void wg_wait() {
  asm volatile("wgmma.wait_group.sync.aligned %0;" ::"n"(n) : "memory");
}
__device__ __forceinline__ uint32_t pack_bf16(float lo, float hi) {
  uint32_t r;
  asm("cvt.rn.bf16x2.f32 %0, %1, %2;" : "=r"(r) : "f"(hi), "f"(lo));
  return r;
}
__device__ __forceinline__ float bf_lo(uint32_t p) { return __uint_as_float(p << 16); }
__device__ __forceinline__ float bf_hi(uint32_t p) { return __uint_as_float(p & 0xffff0000u); }
__device__ __forceinline__ float bf_round(float x) { return __bfloat162float(__float2bfloat16_rn(x)); }
__device__ __forceinline__ uint32_t bf2_add(uint32_t a, uint32_t b) {
  uint32_t r;
  asm("add.rn.bf16x2 %0, %1, %2;" : "=r"(r) : "r"(a), "r"(b));
  return r;
}
__device__ __forceinline__ uint32_t bf2_mul(uint32_t a, uint32_t b) {
  uint32_t r;
  asm("mul.rn.bf16x2 %0, %1, %2;" : "=r"(r) : "r"(a), "r"(b));
  return r;
}
__device__ __forceinline__ uint32_t bf2_fma(uint32_t a, uint32_t b, uint32_t c) {
  uint32_t r;
  asm("fma.rn.bf16x2 %0, %1, %2, %3;" : "=r"(r) : "r"(a), "r"(b), "r"(c));
  return r;
}
__device__ __forceinline__ uint32_t gelu_pack(float a0, float a1, uint32_t hbias2) {
  const uint32_t hp = bf2_fma(pack_bf16(a0, a1), 0x3f003f00u, hbias2);
  const uint32_t q = bf2_fma(bf2_mul(hp, hp), 0x3e923e92u  , 0x3fcc3fccu  );
  uint32_t t;
  asm("tanh.approx.bf16x2 %0, %1;" : "=r"(t) : "r"(bf2_mul(hp, q)));
  return bf2_fma(hp, t, hp);
}

#define R8(a, o) "+f"(a[o]), "+f"(a[o + 1]), "+f"(a[o + 2]), "+f"(a[o + 3]), "+f"(a[o + 4]), "+f"(a[o + 5]), "+f"(a[o + 6]), "+f"(a[o + 7])
#define W8(a, o) "=f"(a[o]), "=f"(a[o + 1]), "=f"(a[o + 2]), "=f"(a[o + 3]), "=f"(a[o + 4]), "=f"(a[o + 5]), "=f"(a[o + 6]), "=f"(a[o + 7])
#define REGS48 "{%0,%1,%2,%3,%4,%5,%6,%7,%8,%9,%10,%11,%12,%13,%14,%15,%16,%17,%18,%19,%20,%21,%22,%23," \
               "%24,%25,%26,%27,%28,%29,%30,%31,%32,%33,%34,%35,%36,%37,%38,%39,%40,%41,%42,%43,%44,%45,%46,%47}"
#define REGS32 "{%0,%1,%2,%3,%4,%5,%6,%7,%8,%9,%10,%11,%12,%13,%14,%15,%16,%17,%18,%19,%20,%21,%22,%23," \
               "%24,%25,%26,%27,%28,%29,%30,%31}"
#define DESC_HI_A  "0x40000040"
#define DESC_HI_B1 "0x80000020"
#define DESC_HI_B2 "0x40000040"
template <bool ACC, int OA, int OB>
__device__ __forceinline__ void wgmma_ss_n96(float (&d)[48], uint32_t da, uint32_t db) {
  if (ACC)
    asm volatile("{\n.reg .b64 xa, xb;\n.reg .b32 la, lb;\nadd.u32 la, %48, %50;\nadd.u32 lb, %49, %51;\n"
                 "mov.b64 xa, {la, " DESC_HI_A "};\nmov.b64 xb, {lb, " DESC_HI_B1 "};\n"
                 "wgmma.mma_async.sync.aligned.m64n96k16.f32.bf16.bf16 " REGS48 ", xa, xb, 1, 1, 1, 0, 1;\n}\n"
                 : R8(d, 0), R8(d, 8), R8(d, 16), R8(d, 24), R8(d, 32), R8(d, 40) : "r"(da), "r"(db), "n"(OA), "n"(OB));
  else
    asm volatile("{\n.reg .b64 xa, xb;\n.reg .b32 la, lb;\nadd.u32 la, %48, %50;\nadd.u32 lb, %49, %51;\n"
                 "mov.b64 xa, {la, " DESC_HI_A "};\nmov.b64 xb, {lb, " DESC_HI_B1 "};\n"
                 "wgmma.mma_async.sync.aligned.m64n96k16.f32.bf16.bf16 " REGS48 ", xa, xb, 0, 1, 1, 0, 1;\n}\n"
                 : W8(d, 0), W8(d, 8), W8(d, 16), W8(d, 24), W8(d, 32), W8(d, 40) : "r"(da), "r"(db), "n"(OA), "n"(OB));
}
template <bool ACC, int OB>
__device__ __forceinline__ void wgmma_rs_n64(float (&d)[32], uint32_t a0, uint32_t a1, uint32_t a2, uint32_t a3, uint32_t db) {
  if (ACC)
    asm volatile("{\n.reg .b64 xb;\n.reg .b32 lb;\nadd.u32 lb, %36, %37;\nmov.b64 xb, {lb, " DESC_HI_B2 "};\n"
                 "wgmma.mma_async.sync.aligned.m64n64k16.f32.bf16.bf16 " REGS32 ", {%32,%33,%34,%35}, xb, 1, 1, 1, 1;\n}\n"
                 : R8(d, 0), R8(d, 8), R8(d, 16), R8(d, 24) : "r"(a0), "r"(a1), "r"(a2), "r"(a3), "r"(db), "n"(OB));
  else
    asm volatile("{\n.reg .b64 xb;\n.reg .b32 lb;\nadd.u32 lb, %36, %37;\nmov.b64 xb, {lb, " DESC_HI_B2 "};\n"
                 "wgmma.mma_async.sync.aligned.m64n64k16.f32.bf16.bf16 " REGS32 ", {%32,%33,%34,%35}, xb, 0, 1, 1, 1;\n}\n"
                 : W8(d, 0), W8(d, 8), W8(d, 16), W8(d, 24) : "r"(a0), "r"(a1), "r"(a2), "r"(a3), "r"(db), "n"(OB));
}
template <int N> __device__ __forceinline__ void fence_regs(float (&d)[N]) {
#pragma unroll
  for (int i = 0; i < N; i++) asm volatile("" : "+f"(d[i])::"memory");
}

constexpr int XS_BYTES = 9 * 16384;
constexpr int STAGE_BYTES = 12288;
constexpr int OFF_ST = XS_BYTES;
constexpr int OFF_B1 = OFF_ST + 6 * STAGE_BYTES;
constexpr int OFF_B2 = OFF_B1 + 1152;
constexpr int OFF_BAR = OFF_B2 + 1152;
constexpr int B_FULL = 0, B_X = 48  , B_RB = 120  , B_OWN = 152, B_FIN = 160, B_A8 = 168, B_OWN2 = 176,
              B_EMPTY = 184  , B_TS = 232  , B_TS8 = 264, B_TR = 272  , B_P1L = 296, B_P1R = 304, B_U = 312,
              B_U0 = 320, NBARS = 41,
              B_CONV = 328, B_COMB = 336;
constexpr int OFF_A8 = OFF_BAR + 512;
constexpr int OFF_ARGS = OFF_A8 + 2048;
constexpr int SMEM_BYTES = OFF_ARGS + 256 + 1024;
constexpr int OFF_STG = 65536, OFF_C8 = 131072;
constexpr int E_UA = 0, E_UB = 3616, E_W3A = 7232, E_W3B = 10848, E_W5 = 14464, E_W9 = 17568, E_TAP = 19680, E_SIZE = 23392;
constexpr int L_W7 = 4752, L_KB = 6832, L_Y = 6848, L_YB = 8304, L_SIZE = 28656;
constexpr int L_CONST = L_Y, L_KC = L_Y + 10240;
constexpr int TP_0 = 0, TP_W3A = 580, TP_UA = 716, TP_UB = 852, TP_W3B = 988, TP_W5 = 1248, TP_W9 = 1448, TP_W7 = 1648,
              TP_COPY = 1856;
__device__ __forceinline__ int e_off(int ch) { return ch == 0 ? 0 : OFF_ST + (ch - 1) * E_SIZE; }
__device__ __forceinline__ int l_off(int ch) { return 32768 + ch * L_SIZE; }
__device__ __forceinline__ int xg_off(int box) { return box < 4 ? OFF_ST + box * 4096 : 170880 + (box - 4) * 4096; }

__device__ __forceinline__ void ln_load(const __nv_bfloat16* __restrict__ x, const __nv_bfloat16* __restrict__ gate_w,
                                        int row, int lane, uint32_t (&w)[9], uint32_t (&gw)[9]) {
  const uint32_t* xr = reinterpret_cast<const uint32_t*>(x + (size_t)row * D_MOD) + lane;
  const uint32_t* gwp = reinterpret_cast<const uint32_t*>(gate_w) + lane;
#pragma unroll
  for (int j = 0; j < 9; j++) {
    asm volatile("ld.global.nc.u32 %0, [%1];" : "=r"(w[j]) : "l"(xr + j * 32));
    asm volatile("ld.global.nc.u32 %0, [%1];" : "=r"(gw[j]) : "l"(gwp + j * 32));
  }
}
__device__ __forceinline__ void ln_row(int row, int lane, const Scratch& sc, const uint32_t (&w)[9], const uint32_t (&gw)[9]) {
  float s = 0.f, gsum = 0.f;
#pragma unroll
  for (int j = 0; j < 9; j++) {
    uint32_t pr2 = bf2_mul(w[j], gw[j]);
    s += bf_lo(w[j]) + bf_hi(w[j]);
    gsum += bf_lo(pr2) + bf_hi(pr2);
  }
#pragma unroll
  for (int o = 1; o < 32; o <<= 1) { s += __shfl_xor_sync(~0u, s, o); gsum += __shfl_xor_sync(~0u, gsum, o); }
  const float mean = s * (1.0f / 576.0f);
  float vs = 0.f;
#pragma unroll
  for (int j = 0; j < 9; j++) {
    float d0 = bf_lo(w[j]) - mean, d1 = bf_hi(w[j]) - mean;
    vs = fmaf(d0, d0, vs); vs = fmaf(d1, d1, vs);
  }
#pragma unroll
  for (int o = 1; o < 32; o <<= 1) vs += __shfl_xor_sync(~0u, vs, o);
  const float mb = bf_round(mean);
  const float vb = bf_round(vs * (1.0f / 576.0f));
  const float rinv = __frcp_rn(bf_round(__fsqrt_rn(bf_round(vb + 1e-5f))));
  const uint32_t nm2 = pack_bf16(-mb, -mb);
  uint32_t* dst = reinterpret_cast<uint32_t*>(sc.xn + (size_t)row * D_MOD) + lane;
#pragma unroll
  for (int j = 0; j < 9; j++) {
    uint32_t dd = bf2_add(w[j], nm2);
    dst[j * 32] = pack_bf16(bf_lo(dd) * rinv, bf_hi(dd) * rinv);
  }
  if (lane == 0) {
    float gv = bf_round(__fdividef(1.0f, 1.0f + __expf(-bf_round(gsum))));
    float og = bf_round(1.0f - gv);
    sc.gate[row] = make_uint2(pack_bf16(gv, gv), pack_bf16(og, og));
  }
}
__device__ __forceinline__ void mma_bf16(float (&d)[4], uint32_t a0, uint32_t a1, uint32_t a2, uint32_t a3, uint32_t b0, uint32_t b1) {
  asm("mma.sync.aligned.m16n8k16.row.col.f32.bf16.bf16.f32 {%0,%1,%2,%3}, {%4,%5,%6,%7}, {%8,%9}, {%0,%1,%2,%3};"
      : "+f"(d[0]), "+f"(d[1]), "+f"(d[2]), "+f"(d[3]) : "r"(a0), "r"(a1), "r"(a2), "r"(a3), "r"(b0), "r"(b1));
}
__device__ __forceinline__ void mma_tf32(float (&d)[4], float a0, float a1, float a2, float a3, float b0, float b1) {
  asm("mma.sync.aligned.m16n8k8.row.col.f32.tf32.tf32.f32 {%0,%1,%2,%3}, {%4,%5,%6,%7}, {%8,%9}, {%0,%1,%2,%3};"
      : "+f"(d[0]), "+f"(d[1]), "+f"(d[2]), "+f"(d[3])
      : "r"(__float_as_uint(a0)), "r"(__float_as_uint(a1)), "r"(__float_as_uint(a2)), "r"(__float_as_uint(a3)),
        "r"(__float_as_uint(b0)), "r"(__float_as_uint(b1)));
}
__device__ __forceinline__ float2 cexp_l(float al, float th, float l) {
  float mg;
  asm("ex2.approx.ftz.f32 %0, %1;" : "=f"(mg) : "f"(al * l));
  const float tr = th * l;
  return make_float2(mg * __cosf(tr), mg * __sinf(tr));
}
__device__ __forceinline__ float2 cmul(float2 a, float2 b) {
  return make_float2(fmaf(a.x, b.x, -a.y * b.y), fmaf(a.x, b.y, a.y * b.x));
}
__device__ __forceinline__ float2 cmulc(float2 a, float2 b) {
  return make_float2(fmaf(a.x, b.x, -a.y * b.y), fmaf(-a.x, b.y, -a.y * b.x));
}
__device__ __forceinline__ float2 csq(float2 a) { return make_float2(fmaf(a.x, a.x, -a.y * a.y), 2.0f * a.x * a.y); }
#define SM_U32(p) (*reinterpret_cast<uint32_t*>(p))
#define SM_F32(p) (*reinterpret_cast<float*>(p))
#define SM_U16(p) (*reinterpret_cast<unsigned short*>(p))
#define SM_U2(p) (*reinterpret_cast<uint2*>(p))
#define SM_F2(p) (*reinterpret_cast<float2*>(p))
#define SM_U4(p) (*reinterpret_cast<uint4*>(p))
#define SM_F4(p) (*reinterpret_cast<float4*>(p))
template <int OFF, int TAG>
__device__ __forceinline__ uint32_t lds_free(uint32_t base) {
  uint32_t v;
  asm volatile("ld.volatile.shared.u32 %0, [%1+%2]; // %3" : "=r"(v) : "r"(base), "n"(OFF), "n"(TAG));
  return v;
}
template <int K0, int K1, int OFF, int K>
__device__ __forceinline__ void load_tquads_(uint32_t (&q)[K1 - K0][4], uint32_t tp) {
  if constexpr (K >= K0) {
    q[K - K0][0] = lds_free<OFF - 32 * K, 0>(tp);
    q[K - K0][1] = lds_free<OFF - 32 * K - 16, 1>(tp);
    q[K - K0][2] = lds_free<OFF - 32 * K + 16, 2>(tp);
    q[K - K0][3] = lds_free<OFF - 32 * K, 3>(tp);
    load_tquads_<K0, K1, OFF, K - 1>(q, tp);
  }
}
template <int K0, int K1, int OFF>
__device__ __forceinline__ void load_tquads(uint32_t (&q)[K1 - K0][4], uint32_t tp) {
  load_tquads_<K0, K1, OFF, K1 - 1>(q, tp);
}
__device__ __forceinline__ void ldsm4_free(uint32_t (&r)[4], uint32_t addr) {
  asm("ldmatrix.sync.aligned.m8n8.x4.shared.b16 {%0,%1,%2,%3}, [%4];"
      : "=r"(r[0]), "=r"(r[1]), "=r"(r[2]), "=r"(r[3]) : "r"(addr));
}
__device__ __forceinline__ void ldsm4t_free(uint32_t (&r)[4], uint32_t addr) {
  asm("ldmatrix.sync.aligned.m8n8.x4.trans.shared.b16 {%0,%1,%2,%3}, [%4];"
      : "=r"(r[0]), "=r"(r[1]), "=r"(r[2]), "=r"(r[3]) : "r"(addr));
}
__device__ __forceinline__ uint32_t ldg_u16(const __nv_bfloat16* p) {
  unsigned short v;
  asm volatile("ld.global.nc.u16 %0, [%1];" : "=h"(v) : "l"(p));
  return v;
}
__device__ __forceinline__ void ldsm4t(uint32_t (&r)[4], uint32_t addr) {
  asm volatile("ldmatrix.sync.aligned.m8n8.x4.trans.shared.b16 {%0,%1,%2,%3}, [%4];"
               : "=r"(r[0]), "=r"(r[1]), "=r"(r[2]), "=r"(r[3]) : "r"(addr) : "memory");
}
template <int I0, int I1, int K0, int K1, int JMIN, int RB, int TOFF>
__device__ __forceinline__ void band(float (&acc)[I1 - I0][4], uint32_t tp, uint32_t sa, uint32_t za, int lane) {
  uint32_t tq[K1 - K0][4];
  load_tquads<K0, K1, TOFF>(tq, tp);
  constexpr int JL = (I0 - K1 + 1 > JMIN) ? I0 - K1 + 1 : JMIN, JH = I1 - 1 - K0;
  constexpr int JP = (JL >= 0) ? (JL & ~1) : -2;
#pragma unroll
  for (int J2 = JP; J2 <= JH; J2 += 2) {
    uint32_t b[4];
    ldsm4t_free(b, (J2 < 0 && lane < 31) ? za : sa + J2 * 16 * RB);
#pragma unroll
    for (int hf = 0; hf < 2; hf++) {
      const int J = J2 + hf;
#pragma unroll
      for (int k = K0; k < K1; k++) {
        const int I = J + k;
        if (J >= JL && J <= JH && I >= I0 && I < I1)
          mma_bf16(acc[I - I0], tq[k - K0][0], tq[k - K0][1], tq[k - K0][2], tq[k - K0][3], b[2 * hf], b[2 * hf + 1]);
      }
    }
  }
}
template <int I0, int I1>
__device__ __forceinline__ void p8_tiles(uint32_t ea, uint32_t za, char* lb, uint32_t tp, int lane) {
  float acc[I1 - I0][4];
#pragma unroll
  for (int i = 0; i < I1 - I0; i++) { acc[i][0] = acc[i][1] = acc[i][2] = acc[i][3] = 0.f; }
  const uint32_t sa = ea + 32 + lane * 16;
  band<I0, I1, 2, 5, -1, 16, TP_W3A + 160>(acc, tp, sa + E_W3A, za, lane);
  band<I0, I1, 2, 5, 0, 16, TP_UA + 160>(acc, tp, sa + E_UA, za, lane);
  band<I0, I1, 2, 5, 0, 16, TP_UB + 160>(acc, tp, sa + E_UB, za, lane);
  band<I0, I1, 2, 9, 0, 16, TP_W3B + 288>(acc, tp, sa + E_W3B, za, lane);
  band<I0, I1, 4, 9, -1, 16, TP_W5 + 288>(acc, tp, sa + E_W5, za, lane);
  char* a = lb + L_Y + L_YB + 4 * (8 * (lane >> 2) + 2 * (lane & 3));
#pragma unroll
  for (int I = I0; I < I1; I++) {
    SM_F2(a + 4 * (128 * I + 4 * (I >> 1))) = make_float2(acc[I - I0][0], acc[I - I0][1]);
    SM_F2(a + 4 * (128 * I + 4 * (I >> 1)) + 256) = make_float2(acc[I - I0][2], acc[I - I0][3]);
  }
}

struct MlpCtx {
  uint32_t bars;
  uint32_t dA, dB;
  int lane;
};
__device__ __forceinline__ void stage_release(const MlpCtx& c, int slot) {
  if (c.lane == 0) mbar_arrive(c.bars + B_EMPTY + 8 * slot);
}
template <int P>
__device__ __forceinline__ void gelu_part(uint32_t baddr, float (&acc)[48]) {
  asm volatile("" : R8(acc, P * 8)::"memory");
  const uint32_t b0 = bf2_mul(lds32(baddr + P * 32), 0x3f003f00u), b1 = bf2_mul(lds32(baddr + P * 32 + 16), 0x3f003f00u);
  uint32_t r0 = gelu_pack(acc[P * 8 + 0], acc[P * 8 + 1], b0);
  uint32_t r1 = gelu_pack(acc[P * 8 + 2], acc[P * 8 + 3], b0);
  uint32_t r2 = gelu_pack(acc[P * 8 + 4], acc[P * 8 + 5], b1);
  uint32_t r3 = gelu_pack(acc[P * 8 + 6], acc[P * 8 + 7], b1);
  acc[P * 8 + 0] = __uint_as_float(r0);
  acc[P * 8 + 1] = __uint_as_float(r1);
  acc[P * 8 + 2] = __uint_as_float(r2);
  acc[P * 8 + 3] = __uint_as_float(r3);
}
__device__ __forceinline__ void h_push(uint32_t (&h)[144], float (&acc)[48]) {
  asm volatile("" : R8(acc, 0)::"memory");
#pragma unroll
  for (int i = 0; i < 96; i++) h[i] = h[i + 24];
#pragma unroll
  for (int i = 0; i < 24; i++) h[96 + i] = __float_as_uint(acc[(i >> 2) * 8 + (i & 3)]);
}
template <int SB, int I>
__device__ __forceinline__ void p1_mma(const MlpCtx& c, float (&cur)[48]) {
  constexpr int S = SB % 9;
  wgmma_ss_n96<(S | I) != 0, ((S * 16384 + I * 32) >> 4),
               (4096 >> 4 << 16) + (((SB % 6) * STAGE_BYTES + I * 1024) >> 4)>(cur, c.dA, c.dB);
}
template <int SB>
__device__ __forceinline__ void p1_stage(const MlpCtx& c, int j, uint32_t baddr, float (&cur)[48], float (&prev)[48],
                                         uint32_t (&h)[144]) {
  constexpr int S = SB % 9;
  if (SB < 9) mbar_wait(c.bars + B_X + 8 * S, 0);
  mbar_wait(c.bars + B_FULL + 8 * (SB % 6), ((SB / 6) + j) & 1);
  WG_FENCE();
  p1_mma<SB, 0>(c, cur); p1_mma<SB, 1>(c, cur); p1_mma<SB, 2>(c, cur); p1_mma<SB, 3>(c, cur);
  WG_COMMIT();
  if (S >= 1 && S <= 6) gelu_part<(S >= 1 && S <= 6) ? S - 1 : 0>(baddr, prev);
  if (S == 7) h_push(h, prev);
  wg_wait<1>();
  if (SB > 0 || j > 0) stage_release(c, (SB + 5) % 6);
  if (S == 0) fence_regs(prev);
}
template <int SB0>
__device__ __forceinline__ void p1_chunk(const MlpCtx& c, int j, uint32_t baddr, float (&cur)[48], float (&prev)[48],
                                         uint32_t (&h)[144]) {
  p1_stage<SB0 + 0>(c, j, baddr, cur, prev, h); p1_stage<SB0 + 1>(c, j, baddr, cur, prev, h);
  p1_stage<SB0 + 2>(c, j, baddr, cur, prev, h); p1_stage<SB0 + 3>(c, j, baddr, cur, prev, h);
  p1_stage<SB0 + 4>(c, j, baddr, cur, prev, h); p1_stage<SB0 + 5>(c, j, baddr, cur, prev, h);
  p1_stage<SB0 + 6>(c, j, baddr, cur, prev, h); p1_stage<SB0 + 7>(c, j, baddr, cur, prev, h);
  p1_stage<SB0 + 8>(c, j, baddr, cur, prev, h);
}
template <int S, int I>
__device__ __forceinline__ void p2_one(const MlpCtx& c, float (&cur)[32], uint32_t (&h)[144]) {
  constexpr int kk = 6 * S + I;
  wgmma_rs_n64<(S | I) != 0, ((S * STAGE_BYTES + I * 2048) >> 4)>(cur, h[4 * kk], h[4 * kk + 1], h[4 * kk + 2], h[4 * kk + 3], c.dB);
}
template <int S>
__device__ __forceinline__ void p2_mma(const MlpCtx& c, uint32_t parity, float (&cur)[32], uint32_t (&h)[144]) {
  mbar_wait(c.bars + B_FULL + 8 * S, parity);
  WG_FENCE();
  p2_one<S, 0>(c, cur, h); p2_one<S, 1>(c, cur, h); p2_one<S, 2>(c, cur, h);
  p2_one<S, 3>(c, cur, h); p2_one<S, 4>(c, cur, h); p2_one<S, 5>(c, cur, h);
  WG_COMMIT();
}
__device__ __forceinline__ int chunk_of(int pos, int pr, int rank) {
  const int off = (int)(0x03231201ull >> (4 * pos)) & 3;
  const int mine = (0x168 >> pos) & 1;
  return pos == 1 ? 8 : 2 * ((pr + off) & 3) + (mine ? rank : rank ^ 1);
}
__device__ __forceinline__ void bulk_s2peer(uint32_t rdst, uint32_t src, uint32_t bytes, uint32_t rbar) {
  asm volatile("cp.async.bulk.shared::cluster.shared::cta.mbarrier::complete_tx::bytes [%0], [%1], %2, [%3];"
               ::"r"(rdst), "r"(src), "r"(bytes), "r"(rbar) : "memory");
}
__device__ __forceinline__ void bulk_s2g_release(void* gdst, uint32_t src, uint32_t bytes) {
  asm volatile("cp.async.bulk.global.shared::cta.bulk_group [%0], [%1], %2;\n"
               "cp.async.bulk.commit_group;\ncp.async.bulk.wait_group 0;\nfence.acq_rel.gpu;"
               ::"l"(gdst), "r"(src), "r"(bytes) : "memory");
}
struct Args {
  const __nv_bfloat16 *u, *Are, *Aim, *Bre, *Bim, *Cre, *Cim, *logdt, *Dskip, *gate_w, *w1, *w2, *b1, *b2;
  __nv_bfloat16* out;
};

struct Maps { const CUtensorMap *x, *w1, *xn; };
__device__ __forceinline__ void load_params(uint32_t (&v)[8], const Args& ar, int d, int n) {
  const int idx = d * N_ST + n;
  v[0] = ldg_u16(ar.Are + idx); v[1] = ldg_u16(ar.Aim + idx); v[2] = ldg_u16(ar.Bre + idx); v[3] = ldg_u16(ar.Bim + idx);
  v[4] = ldg_u16(ar.Cre + idx); v[5] = ldg_u16(ar.Cim + idx); v[6] = ldg_u16(ar.logdt + d); v[7] = ldg_u16(ar.Dskip + d);
}
__device__ __forceinline__ uint4 pack_params(uint32_t (&v)[8]) {
  asm volatile("" : "+r"(v[0]), "+r"(v[1]), "+r"(v[2]), "+r"(v[3]), "+r"(v[4]), "+r"(v[5]), "+r"(v[6]), "+r"(v[7])::"memory");
  return make_uint4(v[0] | (v[1] << 16), v[2] | (v[3] << 16), v[4] | (v[5] << 16), v[6] | (v[7] << 16));
}
__device__ __noinline__ uint4 ssm_pass(const Maps tm, char* sm, const int d0, const int pass, const uint4 pv
) {
  const Args& ar = *reinterpret_cast<const Args*>(sm + OFF_ARGS);
  const Scratch& sc = *reinterpret_cast<const Scratch*>(sm + OFF_ARGS + 128);
  const uint32_t sb = smem_u32(sm), bars = sb + OFF_BAR;
  const int tid = threadIdx.x, lane = tid & 31;
  const int warp = __shfl_sync(0xffffffffu, tid >> 5, 0);
  const int bid = blockIdx.x, m = bid >> 3, f = bid & 7;
  const int g = lane >> 2, cc = lane & 3;
  const int ch = warp >> 2, n = tid & 127;
  char* eb = sm + e_off(ch);
  char* lb = sm + l_off(ch);
#define CH_SYNC() asm volatile("bar.sync %0, 128;" ::"r"(ch + 1) : "memory")
  const bool lead = warp < 8;
  {
    const float are = bf_lo(pv.x), aim = bf_hi(pv.x), bre = bf_lo(pv.y), bim = bf_hi(pv.y);
    const float cre = bf_lo(pv.z), cim = bf_hi(pv.z), ldt = bf_lo(pv.w), dsk = bf_hi(pv.w);
    const float dt = bf_round(expf(ldt));
    const float al = (dt * are) * 1.4426950408889634f, th = dt * aim;
    constexpr float TF32_UNBIAS = 1.0f + 0.7f / 1024.0f;
    const float2 c0 = cmul(make_float2(cre * TF32_UNBIAS, cim * TF32_UNBIAS), make_float2(dt * bre, dt * bim));
    const float2 e64 = cexp_l(al, th, 64.f), e128 = csq(e64), e256 = cexp_l(al, th, 256.f), e512 = csq(e256);
    const float2 k128 = cmul(c0, e128), k256 = cmul(c0, e256), k384 = cmul(k256, e128);
    const float2 k512 = cmul(c0, e512), k516 = cmul(k512, cexp_l(al, th, 4.f));
    const float2 e1024 = cexp_l(al, th, 1024.f), k1024 = cmul(c0, e1024);
    float k2048 = fmaf(k1024.x, e1024.x, -k1024.y * e1024.y) * (1.0f / TF32_UNBIAS);
    char* ca = lb + L_CONST + n * 80;
    SM_F4(ca) = make_float4(al, th, e64.x, e64.y);
    SM_F4(ca + 16) = make_float4(c0.x, c0.y, k128.x, k128.y);
    SM_F4(ca + 32) = make_float4(k256.x, k256.y, k384.x, k384.y);
    SM_F4(ca + 48) = make_float4(k512.x, k512.y, k516.x, k516.y);
    SM_F2(ca + 64) = k1024;
#pragma unroll
    for (int o = 16; o > 0; o >>= 1) k2048 += __shfl_xor_sync(~0u, k2048, o);
    if (lane == 0) SM_F32(lb + L_KC + (warp & 3) * 2576 + 2560) = k2048;
    if (n == 0) SM_F32(lb + L_KB + 8) = dsk;
    __syncwarp();
    DBG_S(0);
    float kd[5][4];
#pragma unroll
    for (int t = 0; t < 5; t++) { kd[t][0] = kd[t][1] = kd[t][2] = kd[t][3] = 0.f; }
    const float l1 = (float)g, l128 = (float)(128 * g);
    const char* cr = lb + L_CONST + ((warp & 3) * 32 + cc) * 80;
    const int o2 = 32 + (g >> 2) * 8, o3 = 48 + (g & 1) * 8, s2 = ((g & 3) << 2) | cc, s3 = ((g >> 1) << 2) | cc;
#pragma unroll 2
    for (int st = 0; st < 8; st++, cr += 320) {
      const float4 q0 = *(const float4*)cr, q1 = *(const float4*)(cr + 16);
      const float2 q2 = *(const float2*)(cr + o2), q3 = *(const float2*)(cr + o3), q4 = *(const float2*)(cr + 64);
      const float2 p1 = cexp_l(q0.x, q0.y, l1), p128 = cexp_l(q0.x, q0.y, l128);
      const float2 p2 = csq(p1), p8 = csq(csq(p2));
      const float2 a1 = cmul(p8, make_float2(q0.z, q0.w));
      float2 x = cmulc(make_float2(q1.x, q1.y), p1);
      mma_tf32(kd[0], p8.x, a1.x, p8.y, a1.y, x.x, x.y);
      x = cmulc(make_float2(q1.z, q1.w), p1);
      mma_tf32(kd[1], p8.x, a1.x, p8.y, a1.y, x.x, x.y);
      x = cmulc(q2, make_float2(__shfl_sync(~0u, p2.x, s2), __shfl_sync(~0u, p2.y, s2)));
      mma_tf32(kd[2], p8.x, a1.x, p8.y, a1.y, x.x, x.y);
      x = cmulc(q3, make_float2(__shfl_sync(~0u, p128.x, s3), __shfl_sync(~0u, p128.y, s3)));
      mma_tf32(kd[3], p8.x, a1.x, p8.y, a1.y, x.x, x.y);
      x = cmulc(q4, p128);
      mma_tf32(kd[4], p8.x, a1.x, p8.y, a1.y, x.x, x.y);
    }
    char* kc = lb + L_KC + (warp & 3) * 2576;
#pragma unroll
    for (int e = 0; e < 2; e++) {
      const int row = g + e * 8;
      SM_F2(kc + 4 * (8 * row + 2 * cc)) = make_float2(kd[0][2 * e], kd[0][2 * e + 1]);
      SM_F2(kc + 4 * (128 + 8 * row + 2 * cc)) = make_float2(kd[1][2 * e], kd[1][2 * e + 1]);
      SM_F2(kc + 4 * (256 + 64 * (cc >> 1) + 4 * row + 2 * (cc & 1))) = make_float2(kd[2][2 * e], kd[2][2 * e + 1]);
      SM_F2(kc + 4 * (384 + 32 * cc + 2 * row)) = make_float2(kd[3][2 * e], kd[3][2 * e + 1]);
      SM_F32(kc + 4 * (512 + 32 * cc + row)) = kd[4][2 * e];
      SM_F32(kc + 4 * (528 + 32 * cc + row)) = kd[4][2 * e + 1];
    }
  }
  DBG_S(1);
  CH_SYNC();
  {
    const char* kc = lb + L_KC;
    auto kq = [&](int idx) {
      const char* q = kc + 4 * idx;
      return (*(const float*)q + *(const float*)(q + 2576)) + (*(const float*)(q + 5152) + *(const float*)(q + 7728));
    };
#pragma unroll
    for (int it = 0; it < 5; it++) {
      const int idx = n + 128 * it;
      float t = kq(idx);
      if ((it == 1 || it == 2) && n == 127) t -= kq(idx + 1);
      if (it == 4 && n == 0) { SM_F2(lb + L_KB) = make_float2(t, kq(640)); t = 0.f; }
      int off;
      if (it < 2) off = TP_0 + 2 * (272 - idx);
      else if (it == 2) {
        const int sel = n & 3, mu = 32 + (n >> 2);
        off = sel == 2 ? TP_W3B + 2 * (144 - mu) : (sel == 0 ? TP_W3A : sel == 1 ? TP_UA : TP_UB) + 2 * (80 - mu);
      } else if (it == 3) off = ((n & 1) ? TP_W3B : TP_W5) + 2 * (80 - (n >> 1));
      else off = ((n & 1) ? TP_W7 : TP_W9) + 2 * (80 - (n >> 1));
      const unsigned short hv = pack_bf16(t, 0.f);
      SM_U16(eb + E_TAP + off) = hv;
      SM_U16(eb + E_TAP + TP_COPY + off + 2) = hv;
    }
  }
  DBG_S(2);
  if (!lead && bid < 128) {
    uint32_t lw[9], lx[9], lg[9];
    const int row = bid * 16 + (warp - 8) * 2;
    ln_load(ar.u, ar.gate_w, row, lane, lw, lg);
    ln_load(ar.u, ar.gate_w, row + 1, lane, lx, lg);
    ln_row(row, lane, sc, lw, lg);
    ln_row(row + 1, lane, sc, lx, lg);
    asm volatile("bar.sync 5, 256;" ::: "memory");
  }
  if (lead) {
    mbar_wait(bars + B_U, pass & 1);
    if (pass > 0) mbar_wait(bars + B_COMB, (pass - 1) & 1);
    const uint32_t src = sb + xg_off(warp) + lane * 16;
    const int mych = g - (d0 & 4);
    char* dst = sm + l_off(mych) + (warp + 1) * 528 + cc * 4;
#pragma unroll
    for (int i = 0; i < 8; i++) {
      uint32_t r[4];
      ldsm4t(r, src + i * 512);
      if (mych >= 0 && mych < 4) {
#pragma unroll
        for (int k = 0; k < 4; k++) SM_U32(dst + i * 64 + k * 16) = r[k];
      }
    }
    __syncwarp();
    if (lane == 0) mbar_arrive(bars + B_U0);
    if (bid < 128 && tid == 0) {
      asm volatile("cp.async.bulk.prefetch.L2.global [%0], %1;" ::"l"(ar.w1 + (size_t)bid * 20736), "r"(41472) : "memory");
      asm volatile("cp.async.bulk.prefetch.L2.global [%0], %1;" ::"l"(ar.w2 + (size_t)bid * 20736), "r"(41472) : "memory");
    }
  }
  DBG_S(3);
  mbar_wait(bars + B_U0, pass & 1);
  DBG_S(4);
#pragma unroll 1
  for (int i = n - 1; i < 224; i += 128) {
    const char* ur = lb + ((i >> 5) + 1) * 528 + (i & 31) * 16;
    const uint4 w0 = *(const uint4*)(ur - ((i & 31) ? 16 : 32) + (i < 0 ? 16 : 0)), w1 = *(const uint4*)ur,
                w2 = *(const uint4*)(ur + ((i & 31) == 31 ? 32 : 16));
    const uint32_t wv[12] = {w0.x, w0.y, w0.z, w0.w, w1.x, w1.y, w1.z, w1.w, w2.x, w2.y, w2.z, w2.w};
    char* o = eb + 32 + 16 * i;
    SM_U4(o + E_UA) = make_uint4(wv[3], wv[4], wv[5], wv[6]);
    SM_U4(o + E_UB) = make_uint4(wv[1], wv[2], wv[3], wv[4]);
    float v[22], wa[16];
#pragma unroll
    for (int k = 1; k < 11; k++) { v[2 * k] = bf_lo(wv[k]); v[2 * k + 1] = bf_hi(wv[k]); }
#pragma unroll
    for (int k = 4; k < 16; k++) wa[k] = (v[k - 1] + v[k]) + v[k + 1];
    SM_U4(o + E_W3A) = make_uint4(pack_bf16(wa[8], wa[9]), pack_bf16(wa[10], wa[11]), pack_bf16(wa[12], wa[13]), pack_bf16(wa[14], wa[15]));
    SM_U4(o + E_W3B) = make_uint4(pack_bf16(wa[4], wa[5]), pack_bf16(wa[6], wa[7]), pack_bf16(wa[8], wa[9]), pack_bf16(wa[10], wa[11]));
    if (i < 192) {
#pragma unroll
      for (int k = 8; k < 16; k++) wa[k] += v[k - 2] + v[k + 2];
      SM_U4(o + E_W5) = make_uint4(pack_bf16(wa[8], wa[9]), pack_bf16(wa[10], wa[11]), pack_bf16(wa[12], wa[13]), pack_bf16(wa[14], wa[15]));
      if (i < 128) {
#pragma unroll
        for (int k = 8; k < 16; k++) wa[k] += v[k - 3] + v[k + 3];
        SM_U4(lb + L_W7 + 32 + 16 * i) =
            make_uint4(pack_bf16(wa[8], wa[9]), pack_bf16(wa[10], wa[11]), pack_bf16(wa[12], wa[13]), pack_bf16(wa[14], wa[15]));
#pragma unroll
        for (int k = 8; k < 16; k++) wa[k] += v[k - 4] + v[k + 4];
        SM_U4(o + E_W9) = make_uint4(pack_bf16(wa[8], wa[9]), pack_bf16(wa[10], wa[11]), pack_bf16(wa[12], wa[13]), pack_bf16(wa[14], wa[15]));
      }
    }
  }
  if (bid < 128 && tid == 480) {
    asm volatile("fence.acq_rel.gpu;" ::: "memory");
    atomicAdd(&sc.flags[256 + m], 1u);
  }
  __syncwarp();
  CH_SYNC();
  DBG_S(5);
  {
    const int role = (warp + ch) & 3;
    uint32_t ea = smem_u32(eb), za = smem_u32(lb);
    asm volatile("" : "+r"(ea), "+r"(za)::"memory");
    const uint32_t tp = ea + E_TAP + ((g & 1) ? TP_COPY + 2 : 0) - 2 * (g - 2 * cc);
    if (role < 2) {
      uint32_t ta[17][4];
      load_tquads<0, 17, TP_0 + 544>(ta, tp);
      float acc[8][4];
#pragma unroll
      for (int i = 0; i < 8; i++) { acc[i][0] = acc[i][1] = acc[i][2] = acc[i][3] = 0.f; }
      const uint32_t bpos = za + ((lane & 7) + 1) * 528 + role * 256 + (lane >> 3) * 16;
      const uint32_t bmid = role ? bpos : bpos - 16;
#pragma unroll
      for (int j2 = -16; j2 < 8; j2 += 2) {
        uint32_t b[4];
        ldsm4_free(b, (j2 < -8 ? bpos - 16 : j2 < 0 ? bmid : bpos) + 32 * j2);
#pragma unroll
        for (int hf = 0; hf < 2; hf++) {
#pragma unroll
          for (int i = 0; i < 8; i++) {
            const int k = i - j2 - hf;
            if (k >= 0 && k <= 16) mma_bf16(acc[i], ta[k][0], ta[k][1], ta[k][2], ta[k][3], b[2 * hf], b[2 * hf + 1]);
          }
        }
      }
      char* ya = lb + L_Y + 4 * (520 * cc + 128 * role + g);
#pragma unroll
      for (int i = 0; i < 8; i++) {
        SM_F32(ya + 64 * i) = acc[i][0]; SM_F32(ya + 64 * i + 1040) = acc[i][1];
        SM_F32(ya + 64 * i + 32) = acc[i][2]; SM_F32(ya + 64 * i + 1072) = acc[i][3];
      }
    } else if (role == 2) {
      p8_tiles<1, 11>(ea, za, lb, tp, lane);
    } else {
      p8_tiles<11, 16>(ea, za, lb, tp, lane);
      float acc[2][5][4];
#pragma unroll
      for (int i = 0; i < 10; i++) { acc[i / 5][i % 5][0] = acc[i / 5][i % 5][1] = acc[i / 5][i % 5][2] = acc[i / 5][i % 5][3] = 0.f; }
#pragma unroll
      for (int sg = 0; sg < 2; sg++) {
        uint32_t tq[5][4];
        if (sg == 0) load_tquads<4, 9, TP_W9 + 288>(tq, tp); else load_tquads<4, 9, TP_W7 + 288>(tq, tp);
        const uint32_t sa = (sg == 0 ? ea + E_W9 : za + L_W7 - 16) + 32 + (lane & 15) * 32 + (lane >> 4) * 16;
#pragma unroll
        for (int J = -1 + sg; J < 4; J++) {
          uint32_t b[4];
          ldsm4t_free(b, (J < 0 && (lane & 15) < 15) ? za : sa + J * 512);
#pragma unroll
          for (int k = 4; k < 9; k++) {
            const int I = J + k;
            if (I < 8) {
              mma_bf16(acc[0][I - 3], tq[k - 4][0], tq[k - 4][1], tq[k - 4][2], tq[k - 4][3], b[0], b[1]);
              mma_bf16(acc[1][I - 3], tq[k - 4][0], tq[k - 4][1], tq[k - 4][2], tq[k - 4][3], b[2], b[3]);
            }
          }
        }
      }
      char* a = lb + L_Y + 2 * L_YB + 4 * (16 * g + 2 * cc);
#pragma unroll
      for (int hh = 0; hh < 2; hh++) {
#pragma unroll
        for (int I = 3; I < 8; I++) {
          SM_F2(a + 32 * hh + 1040 * (I - 3)) = make_float2(acc[hh][I - 3][0], acc[hh][I - 3][1]);
          SM_F2(a + 32 * hh + 1040 * (I - 3) + 512) = make_float2(acc[hh][I - 3][2], acc[hh][I - 3][3]);
        }
      }
    }
  }
  __syncwarp();
  if (lane == 0) {
    mbar_arrive(bars + B_CONV);
    if (!lead) {
      const int iw = warp - 8;
      mbar_wait(bars + B_CONV, pass & 1);
      HFENCE();
      if (bid >= 128) {
        if (pass < 3) {
          mbar_expect_tx(bars + B_U, 4096);
          tma2d(sb + xg_off(iw), tm.x, (d0 + 4) & ~7, iw * 256, bars + B_U);
        }
      } else if (iw < 6) {
        mbar_expect_tx(bars + B_FULL + 8 * iw, STAGE_BYTES);
        tma3d(sb + OFF_ST + iw * STAGE_BYTES, tm.w1, 0, iw * 64, f * 18, bars + B_FULL + 8 * iw);
      } else {
        wait_flag(&sc.flags[256 + m], 8);
        mbar_expect_tx(bars + B_X + 8 * (iw - 6), 16384);
        tma2d(sb + (iw - 6) * 16384, tm.xn, (iw - 6) * 64, m * 128, bars + B_X + 8 * (iw - 6));
      }
    }
  }
  __syncwarp();
  CH_SYNC();
  DBG_S(6);
  uint32_t pnext[8];
#pragma unroll
  for (int i = 0; i < 8; i++) pnext[i] = 0;
  if (bid >= 128 && pass < 3) load_params(pnext, ar, d0 + 4 + ch, n);
  {
    const float4 kb = SM_F4(lb + L_KB);
    const uint32_t dk = pack_bf16(kb.z, kb.z);
#pragma unroll
    for (int k = 0; k < 4; k++) {
      const int t0 = n * 4 + 512 * k;
      char* ya = lb + L_Y + 4 * (t0 + 4 * (t0 >> 8));
      float4 y = SM_F4(ya);
      if (k > 0 || t0 >= 128) { const float4 b = SM_F4(ya + L_YB); y.x += b.x; y.y += b.y; y.z += b.z; y.w += b.w; }
      if (k > 1 || (k == 1 && t0 >= 768)) {
        const float4 b = SM_F4(ya + 2 * L_YB - 3120);
        y.x += b.x; y.y += b.y; y.z += b.z; y.w += b.w;
        if (k > 1 || t0 >= 1020) {
          const char* wp = lb + L_W7 + 32 + 2 * (t0 - 1026);
          const uint32_t wl = *(const uint32_t*)wp, wm = *(const uint32_t*)(wp + 4), wh = *(const uint32_t*)(wp + 8);
          y.x = fmaf(kb.x, bf_hi(wl), y.x); y.y = fmaf(kb.x, bf_lo(wm), y.y);
          y.z = fmaf(kb.x, bf_hi(wm), y.z); y.w = fmaf(kb.x, bf_lo(wh), y.w);
          if (k == 3 && n == 127) {
            const uint2 u03 = SM_U2(lb + 528);
            float pre = bf_lo(u03.x);
            y.x = fmaf(kb.y, pre, y.x); pre += bf_hi(u03.x);
            y.y = fmaf(kb.y, pre, y.y); pre += bf_lo(u03.y);
            y.z = fmaf(kb.y, pre, y.z); pre += bf_hi(u03.y);
            y.w = fmaf(kb.y, pre, y.w);
          }
        }
      }
      const uint2 uu = SM_U2(lb + ((t0 >> 8) + 1) * 528 + (t0 & 255) * 2);
      uint2 o;
      o.x = bf2_add(pack_bf16(y.x, y.y), bf2_mul(uu.x, dk));
      o.y = bf2_add(pack_bf16(y.z, y.w), bf2_mul(uu.y, dk));
      *reinterpret_cast<uint2*>(sc.aT + (size_t)(d0 + ch) * L_SEQ + t0) = o;
    }
  }
  __syncwarp();
  if (lane == 0) mbar_arrive(bars + B_COMB);
  if (lead && bid < 128) {
    asm volatile("bar.sync 6, 256;" ::: "memory");
    if (warp < 3 && lane == 0) {
      HFENCE();
      wait_flag(&sc.flags[256 + m], 8);
      mbar_expect_tx(bars + B_X + 8 * (warp + 2), 16384);
      tma2d(sb + (warp + 2) * 16384, tm.xn, (warp + 2) * 64, m * 128, bars + B_X + 8 * (warp + 2));
    }
    __syncwarp();
  }
  CH_SYNC();
  DBG_S(7);
  return pack_params(pnext);
}

__global__ void __cluster_dims__(2, 1, 1) __launch_bounds__(512, 1)
fused_kernel(const __grid_constant__ CUtensorMap tm_x, const __grid_constant__ CUtensorMap tm_w1,
             const __grid_constant__ CUtensorMap tm_w2, const __grid_constant__ CUtensorMap tm_aT,
             const __grid_constant__ CUtensorMap tm_xn, const __grid_constant__ CUtensorMap tm_out,
             const __grid_constant__ CUtensorMap tm_a8,
             const __grid_constant__ Args ar, const __grid_constant__ Scratch sc) {
  extern __shared__ __align__(1024) char smem_raw[];
  DBG_G(28);
  const uint32_t sb = (smem_u32(smem_raw) + 1023) & ~1023u;
  char* sm = smem_raw + (sb - smem_u32(smem_raw));
  const uint32_t bars = sb + OFF_BAR;
  const int tid = threadIdx.x, lane = tid & 31;
  const int warp = __shfl_sync(0xffffffffu, tid >> 5, 0), wg = warp >> 2;
  const int bid = blockIdx.x;
  const int m = bid >> 3, f = bid & 7, rank = f & 1, pr = f >> 1;

  const int dbase = bid < 128 ? bid * 4 : 512 + (bid - 128) * 16;
  uint32_t praw[8];
  load_params(praw, ar, dbase + wg, tid & 127);

  if (lane == 0) {
    if (warp == 8) {
#pragma unroll
      for (int i = 0; i < B_EMPTY / 8; i++) mbar_init(bars + i * 8, 1);
      asm volatile("fence.mbarrier_init.release.cluster;" ::: "memory");
#pragma unroll
      for (int i = 0; i < 4; i++) mbar_expect_tx(bars + B_RB + 8 * i, 16384);
    } else if (warp == 9) {
#pragma unroll
      for (int i = B_EMPTY / 8; i < NBARS; i++) mbar_init(bars + i * 8, 8);
      mbar_init(bars + B_CONV, 16);
      mbar_init(bars + B_COMB, 16);
      asm volatile("fence.mbarrier_init.release.cluster;" ::: "memory");
    } else if (warp == 10) {
      asm volatile("prefetch.tensormap [%0];" ::"l"(&tm_x) : "memory");
    } else if (warp == 11) {
      *reinterpret_cast<Args*>(sm + OFF_ARGS) = ar;
      *reinterpret_cast<Scratch*>(sm + OFF_ARGS + 128) = sc;
    }
  }
  __syncthreads();
  asm volatile("barrier.cluster.arrive.relaxed.aligned;" ::: "memory");

  {
    Maps tm;
    tm.x = &tm_x; tm.w1 = &tm_w1; tm.xn = &tm_xn;
    const int npass = bid < 128 ? 1 : 4;
    if (lane == 0 && (warp & 1) == 0) {
      mbar_expect_tx(bars + B_U, 4096);
      tma2d(sb + xg_off(warp >> 1), &tm_x, dbase & ~7, (warp >> 1) * 256, bars + B_U);
    }
    {
      char* eb = sm + e_off(wg);
      const int n = tid & 127;
      const uint4 z = make_uint4(0, 0, 0, 0);
      SM_U4(eb + E_TAP + n * 16) = z;
      if (n < 104) SM_U4(eb + E_TAP + 2048 + n * 16) = z;
      else if (n == 104) SM_U4(eb + E_W9) = z;
      if (n < 33) SM_U4(sm + l_off(wg) + n * 16) = z;
    }
    uint4 pv = pack_params(praw);
#pragma unroll 1
    for (int pass = 0; pass < npass; pass++)
      pv = ssm_pass(tm, sm, dbase + pass * 4, pass, pv
      );
  }
  __syncthreads();
  if (bid >= 128) {
    if (tid == 0) {
      asm volatile("fence.acq_rel.gpu;" ::: "memory");
      atomicAdd(&sc.flags[304], 1u);
    }
    __syncwarp();
    asm volatile("barrier.cluster.wait.acquire.aligned;" ::: "memory");
    return;
  }

  const uint32_t rdelta = mapa(sb, rank ^ 1) - sb;
  if (wg >= 2) {
    asm volatile("setmaxnreg.dec.sync.aligned.u32 24;");
    asm volatile("barrier.cluster.wait.acquire.aligned;" ::: "memory");
    const int pw = warp - 8;
    if (lane == 0) {
      if (pw < 2) {
        int slot = pw, par = 0;
#pragma unroll 1
        for (int it = 6 + pw; it < 54; it += 2) {
          const int ch = it / 9, s = it - ch * 9;
          const uint32_t fb = bars + B_FULL + 8 * slot;
          mbar_wait(bars + B_EMPTY + 8 * slot, par);
          mbar_expect_tx(fb, STAGE_BYTES);
          tma3d(sb + OFF_ST + slot * STAGE_BYTES, &tm_w1, 0, s * 64, f * 18 + ch * 3, fb);
          slot += 2;
          if (slot >= 6) { slot -= 6; par ^= 1; }
        }
#pragma unroll 1
        for (int pos = 0; pos < 9; pos++) {
          const int chunk = chunk_of(pos, pr, rank);
#pragma unroll 1
          for (slot = pw; slot < 6; slot += 2) {
            const uint32_t fb = bars + B_FULL + 8 * slot;
            mbar_wait(bars + B_EMPTY + 8 * slot, par);
            mbar_expect_tx(fb, STAGE_BYTES);
            tma2d(sb + OFF_ST + slot * STAGE_BYTES, &tm_w2, chunk * 64, f * 576 + slot * 96, fb);
          }
          par ^= 1;
        }
        if (pw == 0) {
          wait_flag(&sc.flags[288 + f * 2], 16);
          mbar_wait(bars + B_EMPTY, par);
          mbar_wait(bars + B_EMPTY + 8, par);
          mbar_expect_tx(bars + B_FULL, 16384);
          tma2d(sb + OFF_ST, &tm_aT, m * 128, f * 64, bars + B_FULL);
          tma2d(sb + OFF_ST + 8192, &tm_aT, m * 128 + 64, f * 64, bars + B_FULL);
          if (atomicAdd(&sc.flags[289 + f * 2], 1u) == 15) { sc.flags[288 + f * 2] = 0; sc.flags[289 + f * 2] = 0; }
        }
      } else if (pw == 2) {
        mbar_wait(bars + B_P1R, 0);
#pragma unroll 1
        for (int k = 0; k < 4; k++) {
          mbar_wait(bars + B_TS + 8 * k, 0);
          HFENCE();
          bulk_s2peer(sb + k * 16384 + rdelta, sb + OFF_STG + k * 16384, 16384, bars + B_RB + 8 * k + rdelta);
        }
#pragma unroll 1
        for (int k = 0; k < 4; k++) mbar_wait(bars + B_RB + 8 * k, 0);
        mbar_arrive_remote(bars + B_FIN + rdelta);
        mbar_wait(bars + B_FIN, 0);
      } else if (pw == 3) {
        mbar_wait(bars + B_TS8, 0);
        HFENCE();
        bulk_s2g_release(sc.slots8 + (size_t)(m * 8 + f) * 4096, sb + OFF_C8, 16384);
#pragma unroll 1
        for (int i = 0; i < 8; i++) atomicAdd(&sc.flags[m * 16 + 8 + i], 1u);
#pragma unroll 1
        for (int k = 0; k < 2; k++) {
          const int chunk = 2 * ((pr + k + 1) & 3) + rank;
          mbar_wait(bars + B_TR + 8 * k, 0);
          HFENCE();
          bulk_s2g_release(sc.slots + (size_t)((m * 8 + chunk) * 3 + k) * 4096, sb + k * 16384, 16384);
          atomicAdd(&sc.flags[320 + (m * 8 + chunk) * 4 + k], 1u);
          DBG_H(16 + k);
          if (k == 0) {
            mbar_expect_tx(bars + B_OWN, 49152);
            wait_flag(&sc.flags[m * 16 + 8 + f], 8);
            sc.flags[m * 16 + 8 + f] = 0;
#pragma unroll 1
            for (int i = 0; i < 8; i++)
              bulk_g2s(sb + OFF_C8 + i * 2048, sc.slots8 + (size_t)(m * 8 + i) * 4096 + f * 512, 2048, bars + B_OWN);
          }
        }
#pragma unroll 1
        for (int j = 0; j < 2; j++) {
          unsigned int* fl = &sc.flags[320 + (m * 8 + f) * 4 + j];
          wait_flag(fl, 1);
          *fl = 0;
          bulk_g2s(sb + j * 16384, sc.slots + (size_t)((m * 8 + f) * 3 + j) * 4096, 16384, bars + B_OWN);
        }
        if (f == 0) sc.flags[256 + m] = 0;
        DBG_H(19);
      } else if (pw == 4) {
        asm volatile("fence.acq_rel.gpu;" ::: "memory");
        atomicAdd(&sc.flags[288 + (bid >> 4) * 2], 1u);
        mbar_wait(bars + B_TR + 8, 0);
        wait_flag(&sc.flags[304], 4);
        mbar_expect_tx(bars + B_A8, 2048);
        tma2d(sb + OFF_A8, &tm_a8, m * 128, 512 + f * 8, bars + B_A8);
        if (atomicAdd(&sc.flags[305], 1u) == 127) { sc.flags[304] = 0; sc.flags[305] = 0; }
      } else {
        HFENCE();
#pragma unroll 1
        for (int kb = pw; kb < 9; kb += 3) {
          mbar_expect_tx(bars + B_X + 8 * kb, kb == 8 ? 16384 + 2304 : 16384);
          tma2d(sb + kb * 16384, &tm_xn, kb * 64, m * 128, bars + B_X + 8 * kb);
          if (kb == 8) {
            bulk_g2s(sb + OFF_B1, ar.b1 + f * 576, 1152, bars + B_X + 64);
            bulk_g2s(sb + OFF_B2, ar.b2, 1152, bars + B_X + 64);
          }
        }
        if (pw == 6) {
          const int chunk = 2 * ((pr + 3) & 3) + rank;
          mbar_wait(bars + B_TR + 16, 0);
          HFENCE();
          bulk_s2g_release(sc.slots + (size_t)((m * 8 + chunk) * 3 + 2) * 4096, sb + 32768, 16384);
          atomicAdd(&sc.flags[320 + (m * 8 + chunk) * 4 + 2], 1u);
          DBG_H(18);
          unsigned int* fl = &sc.flags[320 + (m * 8 + f) * 4 + 2];
          mbar_expect_tx(bars + B_OWN2, 16384);
          wait_flag(fl, 1);
          *fl = 0;
          bulk_g2s(sb + 32768, sc.slots + (size_t)((m * 8 + f) * 3 + 2) * 4096, 16384, bars + B_OWN2);
        }
      }
    }
  } else {
    asm volatile("setmaxnreg.inc.sync.aligned.u32 232;");
    const int wi = warp & 3;
    DBG_T(0);
    MlpCtx c;
    c.bars = bars; c.lane = lane;
    c.dA = (((sb + wg * 8192) & 0x3FFFF) >> 4) | (1u << 16);
    c.dB = ((sb + OFF_ST) & 0x3FFFF) >> 4;

    uint32_t h[144];
    float acc2a[32], acc2b[32];
    {
      float accA[48], accB[48];
#pragma unroll
      for (int i = 0; i < 48; i++) { accA[i] = 0.f; accB[i] = 0.f; }
#pragma unroll
      for (int i = 0; i < 144; i++) h[i] = 0;
      uint32_t baddr = sb + OFF_B1 + (lane & 3) * 4 - 192;
#pragma unroll 1
      for (int j = 0; j < 3; j++) {
        DBG_T(11 + 2 * j);
        p1_chunk<0>(c, j, baddr, accA, accB, h);
        baddr += 192;
        DBG_T(10 + 2 * j);
        p1_chunk<9>(c, j, baddr, accB, accA, h);
        baddr += 192;
      }
      DBG_T(2);
      p2_mma<0>(c, 1, acc2a, h);
      wg_wait<1>();
      stage_release(c, 5);
      fence_regs(accB);
      asm volatile("barrier.cluster.wait.acquire.aligned;" ::: "memory");
      if (lane == 0) { mbar_arrive(bars + B_P1L); mbar_arrive_remote(bars + B_P1R + rdelta); }
      p2_mma<1>(c, 1, acc2a, h);
      gelu_part<0>(baddr, accB); gelu_part<1>(baddr, accB);
      wg_wait<1>(); stage_release(c, 0);
      p2_mma<2>(c, 1, acc2a, h);
      gelu_part<2>(baddr, accB); gelu_part<3>(baddr, accB);
      wg_wait<1>(); stage_release(c, 1);
      p2_mma<3>(c, 1, acc2a, h);
      gelu_part<4>(baddr, accB);
      wg_wait<1>(); stage_release(c, 2);
      p2_mma<4>(c, 1, acc2a, h);
      gelu_part<5>(baddr, accB);
#pragma unroll
      for (int i = 0; i < 24; i++) h[120 + i] = __float_as_uint(accB[(i >> 2) * 8 + (i & 3)]);
      wg_wait<1>(); stage_release(c, 3);
      p2_mma<5>(c, 1, acc2a, h);
      wg_wait<1>(); stage_release(c, 4);
    }
    const uint32_t lbuf = sb + warp * 2048 + lane * 16;
    mbar_wait(bars + B_P1L, 0);
#pragma unroll 1
    for (int pos = 0; pos < 8; pos++) {
      const bool recv = (0x68 >> pos) & 1;
      const int k = recv ? (pos - 2) >> 1 : (pos + 1) >> 1;
      const int ks = k > 3 ? 3 : k;
      const uint32_t addr = lbuf + ks * 16384 + (recv ? 0 : OFF_STG);
      const uint32_t sig = bars + (recv ? B_TR + 8 * k : pos == 1 ? B_TS8 : B_TS + 8 * ks);
      if (recv) mbar_wait(bars + B_RB + k * 8, 0);
      wg_wait<0>(); stage_release(c, 5);
      fence_regs(acc2a);
      DBG_T(20 + pos);
      if (recv) {
#pragma unroll
        for (int i = 0; i < 4; i++) {
          const float4 r = lds128f(addr + i * 512);
          const uint32_t w0 = __float_as_uint(r.x), w1 = __float_as_uint(r.y), w2 = __float_as_uint(r.z), w3 = __float_as_uint(r.w);
          acc2a[8 * i + 0] += bf_lo(w0); acc2a[8 * i + 1] += bf_hi(w0); acc2a[8 * i + 2] += bf_lo(w1); acc2a[8 * i + 3] += bf_hi(w1);
          acc2a[8 * i + 4] += bf_lo(w2); acc2a[8 * i + 5] += bf_hi(w2); acc2a[8 * i + 6] += bf_lo(w3); acc2a[8 * i + 7] += bf_hi(w3);
        }
      }
      if (pos == 1) {
        const uint32_t a8 = sb + OFF_C8 + warp * 256 + lane * 8;
#pragma unroll
        for (int q = 0; q < 8; q++)
          asm volatile("st.shared.v2.u32 [%0], {%1,%2};" ::"r"(a8 + q * 2048), "r"(pack_bf16(acc2a[4 * q], acc2a[4 * q + 1])),
                       "r"(pack_bf16(acc2a[4 * q + 2], acc2a[4 * q + 3])) : "memory");
      } else {
#pragma unroll
        for (int i = 0; i < 4; i++)
          sts128(addr + i * 512, pack_bf16(acc2a[8 * i], acc2a[8 * i + 1]), pack_bf16(acc2a[8 * i + 2], acc2a[8 * i + 3]),
                 pack_bf16(acc2a[8 * i + 4], acc2a[8 * i + 5]), pack_bf16(acc2a[8 * i + 6], acc2a[8 * i + 7]));
      }
      const uint32_t par = pos & 1;
      p2_mma<0>(c, par, acc2a, h);
      __syncwarp();
      if (lane == 0) mbar_arrive(sig);
      p2_mma<1>(c, par, acc2a, h);
      wg_wait<1>(); stage_release(c, 0);
      p2_mma<2>(c, par, acc2a, h);
      wg_wait<1>(); stage_release(c, 1);
      p2_mma<3>(c, par, acc2a, h);
      wg_wait<1>(); stage_release(c, 2);
      p2_mma<4>(c, par, acc2a, h);
      wg_wait<1>(); stage_release(c, 3);
      p2_mma<5>(c, par, acc2a, h);
      wg_wait<1>(); stage_release(c, 4);
    }
    DBG_T(3);
    {
      const int g = lane >> 2, cc = lane & 3;
      const int t0 = m * 128 + warp * 16 + g;
      const uint2 ga = __ldcg(&sc.gate[t0]), gb = __ldcg(&sc.gate[t0 + 8]);
#pragma unroll
      for (int i = 0; i < 32; i++) acc2b[i] = 0.f;
      auto add_tile = [&](int k) {
#pragma unroll
        for (int i = 0; i < 4; i++) {
          float4 r = lds128f(lbuf + k * 16384 + i * 512);
          const uint32_t w0 = __float_as_uint(r.x), w1 = __float_as_uint(r.y), w2 = __float_as_uint(r.z), w3 = __float_as_uint(r.w);
          acc2b[8 * i + 0] += bf_lo(w0); acc2b[8 * i + 1] += bf_hi(w0); acc2b[8 * i + 2] += bf_lo(w1); acc2b[8 * i + 3] += bf_hi(w1);
          acc2b[8 * i + 4] += bf_lo(w2); acc2b[8 * i + 5] += bf_hi(w2); acc2b[8 * i + 6] += bf_lo(w3); acc2b[8 * i + 7] += bf_hi(w3);
        }
      };
      mbar_wait(bars + B_OWN, 0);
      add_tile(0);
      add_tile(1);
      float c8[4] = {0.f, 0.f, 0.f, 0.f};
#pragma unroll
      for (int i = 0; i < 8; i++) {
        uint32_t w0, w1;
        asm volatile("ld.shared.v2.u32 {%0,%1}, [%2];" : "=r"(w0), "=r"(w1) : "r"(sb + OFF_C8 + i * 2048 + warp * 256 + lane * 8));
        c8[0] += bf_lo(w0); c8[1] += bf_hi(w0); c8[2] += bf_lo(w1); c8[3] += bf_hi(w1);
      }
      mbar_wait(bars + B_RB + 24, 0);
      add_tile(3);
      mbar_wait(bars + B_OWN2, 0);
      DBG_T(8);
      add_tile(2);
      DBG_T(9);
      mbar_wait(bars + B_FULL, 0);
      wg_wait<0>();
      fence_regs(acc2a);
      DBG_T(4);
#pragma unroll
      for (int jj = 0; jj < 4; jj++) {
        uint32_t a[4];
        {
          const int dl = 8 * (2 * jj + (lane >> 4)) + (lane & 7);
          const int chk = 2 * wi + ((lane >> 3) & 1);
          ldsm4t(a, sb + OFF_ST + wg * 8192 + dl * 128 + ((chk ^ (dl & 7)) << 4));
        }
        uint32_t o[4];
#pragma unroll
        for (int e = 0; e < 2; e++) {
          const int q = 2 * jj + e;
          uint32_t bb = lds32(sb + OFF_B2 + (f * 64 + q * 8 + cc * 2) * 2);
          uint32_t v0 = bf2_add(pack_bf16(acc2a[4 * q] + acc2b[4 * q], acc2a[4 * q + 1] + acc2b[4 * q + 1]), bb);
          uint32_t v1 = bf2_add(pack_bf16(acc2a[4 * q + 2] + acc2b[4 * q + 2], acc2a[4 * q + 3] + acc2b[4 * q + 3]), bb);
          o[2 * e] = bf2_add(bf2_mul(ga.x, a[2 * e]), bf2_mul(ga.y, v0));
          o[2 * e + 1] = bf2_add(bf2_mul(gb.x, a[2 * e + 1]), bf2_mul(gb.y, v1));
        }
        {
          const int row = (lane & 7) + ((lane >> 3) & 1) * 8;
          const uint32_t addr = sb + 49152 + warp * 2048 + row * 128 + (((2 * jj + (lane >> 4)) ^ (row & 7)) << 4);
          asm volatile("stmatrix.sync.aligned.m8n8.x4.shared.b16 [%0], {%1,%2,%3,%4};"
                       ::"r"(addr), "r"(o[0]), "r"(o[1]), "r"(o[2]), "r"(o[3]) : "memory");
        }
      }
      asm volatile("fence.proxy.async.shared::cta;" ::: "memory");
      __syncwarp();
      if (lane == 0) {
        asm volatile("cp.async.bulk.tensor.2d.global.shared::cta.bulk_group [%0, {%2, %3}], [%1];\n"
                     "cp.async.bulk.commit_group;"
                     ::"l"(&tm_out), "r"(sb + 49152 + warp * 2048), "r"(f * 64), "r"(m * 128 + warp * 16) : "memory");
      }
      __syncwarp();
      mbar_wait(bars + B_A8, 0);
      {
        __nv_bfloat16* op = ar.out + (size_t)t0 * D_MOD + cc * 2 + 512 + f * 8;
        uint32_t a0, a1;
        const uint32_t addr = sb + OFF_A8 + (lane & 7) * 256 + (warp * 2 + ((lane >> 3) & 1)) * 16;
        asm volatile("ldmatrix.sync.aligned.m8n8.x2.trans.shared.b16 {%0,%1}, [%2];" : "=r"(a0), "=r"(a1) : "r"(addr));
        const uint32_t bb = lds32(sb + OFF_B2 + (512 + f * 8 + cc * 2) * 2);
        const uint32_t v0 = bf2_add(pack_bf16(c8[0], c8[1]), bb), v1 = bf2_add(pack_bf16(c8[2], c8[3]), bb);
        *reinterpret_cast<uint32_t*>(op) = bf2_add(bf2_mul(ga.x, a0), bf2_mul(ga.y, v0));
        *reinterpret_cast<uint32_t*>(op + 8 * D_MOD) = bf2_add(bf2_mul(gb.x, a1), bf2_mul(gb.y, v1));
      }
      if (lane == 0) asm volatile("cp.async.bulk.wait_group.read 0;" ::: "memory");
      DBG_T(5);
      DBG_G(29);
    }
  }
}

typedef CUresult (*EncodeTiledFn)(CUtensorMap*, CUtensorMapDataType, cuuint32_t, void*, const cuuint64_t*,
                                  const cuuint64_t*, const cuuint32_t*, const cuuint32_t*, CUtensorMapInterleave,
                                  CUtensorMapSwizzle, CUtensorMapL2promotion, CUtensorMapFloatOOBfill);

static void make_map(EncodeTiledFn enc, CUtensorMap* tm, const void* base, uint64_t inner, uint64_t outer, uint32_t binner,
                     uint32_t bouter, CUtensorMapSwizzle swz) {
  cuuint64_t gd[2] = {inner, outer};
  cuuint64_t gs[1] = {inner * 2};
  cuuint32_t bd[2] = {binner, bouter};
  cuuint32_t es[2] = {1, 1};
  enc(tm, CU_TENSOR_MAP_DATA_TYPE_BFLOAT16, 2, const_cast<void*>(base), gd, gs, bd, es, CU_TENSOR_MAP_INTERLEAVE_NONE, swz,
      CU_TENSOR_MAP_L2_PROMOTION_L2_128B, CU_TENSOR_MAP_FLOAT_OOB_FILL_NONE);
}

extern "C" void kernel_launch(void* const* d_in, const int* in_sizes, int n_in, void* d_out, int out_size) {
  typedef const __nv_bfloat16* BP;
  Args ar;
  ar.u = (BP)d_in[0]; ar.Are = (BP)d_in[1]; ar.Aim = (BP)d_in[2]; ar.Bre = (BP)d_in[3]; ar.Bim = (BP)d_in[4];
  ar.Cre = (BP)d_in[5]; ar.Cim = (BP)d_in[6]; ar.logdt = (BP)d_in[7]; ar.Dskip = (BP)d_in[8];
  ar.w1 = (BP)d_in[10]; ar.b1 = (BP)d_in[11]; ar.w2 = (BP)d_in[12]; ar.b2 = (BP)d_in[13]; ar.gate_w = (BP)d_in[14];
  ar.out = (__nv_bfloat16*)d_out;

  static EncodeTiledFn enc = nullptr;
  static Scratch sc;
  if (!enc) {
    cudaDriverEntryPointQueryResult qr;
    cudaGetDriverEntryPoint("cuTensorMapEncodeTiled", (void**)&enc, cudaEnableDefault, &qr);
    cudaGetSymbolAddress((void**)&sc.aT, g_aT);
    cudaGetSymbolAddress((void**)&sc.xn, g_xn);
    cudaGetSymbolAddress((void**)&sc.gate, g_gate);
    cudaGetSymbolAddress((void**)&sc.slots, g_slots);
    cudaGetSymbolAddress((void**)&sc.slots8, g_slots8);
    cudaGetSymbolAddress((void**)&sc.flags, g_flags);
    sc.dbg = nullptr;
    cudaFuncSetAttribute(fused_kernel, cudaFuncAttributeMaxDynamicSharedMemorySize, SMEM_BYTES);
  }
  CUtensorMap tm_x, tm_w1, tm_w2, tm_aT, tm_xn, tm_out, tm_a8;
  make_map(enc, &tm_a8, sc.aT, L_SEQ, D_MOD, 128, 8, CU_TENSOR_MAP_SWIZZLE_NONE);
  make_map(enc, &tm_x, ar.u, D_MOD, L_SEQ, 8, 256, CU_TENSOR_MAP_SWIZZLE_NONE);
  make_map(enc, &tm_w2, ar.w2, D_MOD, F_HID, 64, 96, CU_TENSOR_MAP_SWIZZLE_128B);
  make_map(enc, &tm_aT, sc.aT, L_SEQ, D_MOD, 64, 64, CU_TENSOR_MAP_SWIZZLE_128B);
  make_map(enc, &tm_xn, sc.xn, D_MOD, L_SEQ, 64, 128, CU_TENSOR_MAP_SWIZZLE_128B);
  make_map(enc, &tm_out, d_out, D_MOD, L_SEQ, 64, 16, CU_TENSOR_MAP_SWIZZLE_128B);
  {
    cuuint64_t gd[3] = {32, D_MOD, F_HID / 32};
    cuuint64_t gs[2] = {F_HID * 2, 64};
    cuuint32_t bd[3] = {32, 64, 3};
    cuuint32_t es[3] = {1, 1, 1};
    enc(&tm_w1, CU_TENSOR_MAP_DATA_TYPE_BFLOAT16, 3, (void*)ar.w1, gd, gs, bd, es, CU_TENSOR_MAP_INTERLEAVE_NONE,
        CU_TENSOR_MAP_SWIZZLE_64B, CU_TENSOR_MAP_L2_PROMOTION_L2_128B, CU_TENSOR_MAP_FLOAT_OOB_FILL_NONE);
  }
  fused_kernel<<<132, 512, SMEM_BYTES, cudaStreamPerThread>>>(tm_x, tm_w1, tm_w2, tm_aT, tm_xn, tm_out, tm_a8, ar, sc);
}
```

```cpp
#include <cuda_runtime.h>
#include <cuda_bf16.h>
#include <cuda.h>
#include <stdint.h>

#define HFENCE() asm volatile("fence.proxy.async.shared::cta;" ::: "memory")
#define HO2 1
#define L_SEQ 2048
#define D_MOD 576
#define F_HID 4608
#define N_ST 128

__device__ __align__(1024) __nv_bfloat16 g_aT[D_MOD * L_SEQ];
__device__ __align__(1024) __nv_bfloat16 g_xn[L_SEQ * D_MOD];
__device__ __align__(1024) uint32_t g_slots[16 * 8 * 3 * 4096];
__device__ __align__(1024) uint32_t g_slots8[16 * 8 * 4096];
__device__ uint2 g_gate[L_SEQ];
__device__ unsigned int g_flags[832];
struct Scratch {
  __nv_bfloat16* aT; __nv_bfloat16* xn; uint2* gate; uint32_t* slots; uint32_t* slots8; unsigned int* flags;
  long long* dbg;
};
#define DBG_T(i)
#define DBG_S(i)
#define DBG_H(i)
#define DBG_G(i)

__device__ __forceinline__ uint32_t smem_u32(const void* p) { return (uint32_t)__cvta_generic_to_shared(p); }
__device__ __forceinline__ void mbar_init(uint32_t bar, int cnt) {
  asm volatile("mbarrier.init.shared::cta.b64 [%0], %1;" ::"r"(bar), "r"(cnt));
}
__device__ __forceinline__ void mbar_expect_tx(uint32_t bar, uint32_t bytes) {
  asm volatile("mbarrier.arrive.expect_tx.shared::cta.b64 _, [%0], %1;" ::"r"(bar), "r"(bytes) : "memory");
}
__device__ __forceinline__ void mbar_arrive(uint32_t bar) {
  asm volatile("mbarrier.arrive.shared::cta.b64 _, [%0];" ::"r"(bar) : "memory");
}
__device__ __forceinline__ void mbar_arrive_remote(uint32_t remote_bar) {
  asm volatile("mbarrier.arrive.relaxed.cluster.shared::cluster.b64 _, [%0];" ::"r"(remote_bar) : "memory");
}
__device__ __forceinline__ void mbar_wait(uint32_t bar, uint32_t parity) {
  asm volatile(
      "{\n.reg .pred p;\n.reg .u32 n;\nmov.u32 n, 0;\n"
      "W_%=:\nmbarrier.try_wait.parity.shared::cta.b64 p, [%0], %1;\n@p bra D_%=;\n"
      "add.u32 n, n, 1;\nsetp.lt.u32 p, n, 400000;\n@p bra W_%=;\ntrap;\nD_%=:\n}"
      ::"r"(bar), "r"(parity) : "memory");
}
__device__ __forceinline__ void tma2d(uint32_t dst, const CUtensorMap* tm, int c0, int c1, uint32_t bar) {
  asm volatile("cp.async.bulk.tensor.2d.shared::cluster.global.mbarrier::complete_tx::bytes [%0], [%1, {%3, %4}], [%2];"
               ::"r"(dst), "l"(tm), "r"(bar), "r"(c0), "r"(c1) : "memory");
}
__device__ __forceinline__ void wait_flag(unsigned int* flag, unsigned int target) {
  asm volatile(
      "{\n.reg .pred p;\n.reg .u32 n, v;\nmov.u32 n, 0;\n"
      "W_%=:\nld.acquire.gpu.global.u32 v, [%0];\nsetp.ge.u32 p, v, %1;\n@p bra D_%=;\n"
      "nanosleep.u32 32;\nadd.u32 n, n, 1;\nsetp.lt.u32 p, n, 4000000;\n@p bra W_%=;\ntrap;\nD_%=:\n}"
      ::"l"(flag), "r"(target) : "memory");
}
__device__ __forceinline__ void bulk_g2s(uint32_t dst, const void* src, uint32_t bytes, uint32_t bar) {
  asm volatile("cp.async.bulk.shared::cluster.global.mbarrier::complete_tx::bytes [%0], [%1], %2, [%3];"
               ::"r"(dst), "l"(src), "r"(bytes), "r"(bar) : "memory");
}
__device__ __forceinline__ void tma3d(uint32_t dst, const CUtensorMap* tm, int c0, int c1, int c2, uint32_t bar) {
  asm volatile("cp.async.bulk.tensor.3d.shared::cluster.global.mbarrier::complete_tx::bytes [%0], [%1, {%3, %4, %5}], [%2];"
               ::"r"(dst), "l"(tm), "r"(bar), "r"(c0), "r"(c1), "r"(c2) : "memory");
}
__device__ __forceinline__ uint32_t mapa(uint32_t addr, uint32_t rank) {
  uint32_t r;
  asm("mapa.shared::cluster.u32 %0, %1, %2;" : "=r"(r) : "r"(addr), "r"(rank));
  return r;
}
__device__ __forceinline__ float4 lds128f(uint32_t addr) {
  float4 v;
  asm volatile("ld.shared.v4.f32 {%0,%1,%2,%3}, [%4];" : "=f"(v.x), "=f"(v.y), "=f"(v.z), "=f"(v.w) : "r"(addr));
  return v;
}
__device__ __forceinline__ uint32_t lds32(uint32_t addr) {
  uint32_t v;
  asm volatile("ld.shared.u32 %0, [%1];" : "=r"(v) : "r"(addr));
  return v;
}
__device__ __forceinline__ void sts128(uint32_t addr, uint32_t a, uint32_t b, uint32_t c, uint32_t d) {
  asm volatile("st.shared.v4.u32 [%0], {%1,%2,%3,%4};" ::"r"(addr), "r"(a), "r"(b), "r"(c), "r"(d) : "memory");
}
#define WG_FENCE() asm volatile("wgmma.fence.sync.aligned;" ::: "memory")
#define WG_COMMIT() asm volatile("wgmma.commit_group.sync.aligned;" ::: "memory")
template <int n> __device__ __forceinline__ void wg_wait() {
  asm volatile("wgmma.wait_group.sync.aligned %0;" ::"n"(n) : "memory");
}
__device__ __forceinline__ uint32_t pack_bf16(float lo, float hi) {
  uint32_t r;
  asm("cvt.rn.bf16x2.f32 %0, %1, %2;" : "=r"(r) : "f"(hi), "f"(lo));
  return r;
}
__device__ __forceinline__ float bf_lo(uint32_t p) { return __uint_as_float(p << 16); }
__device__ __forceinline__ float bf_hi(uint32_t p) { return __uint_as_float(p & 0xffff0000u); }
__device__ __forceinline__ float bf_round(float x) { return __bfloat162float(__float2bfloat16_rn(x)); }
__device__ __forceinline__ uint32_t bf2_add(uint32_t a, uint32_t b) {
  uint32_t r;
  asm("add.rn.bf16x2 %0, %1, %2;" : "=r"(r) : "r"(a), "r"(b));
  return r;
}
__device__ __forceinline__ uint32_t bf2_mul(uint32_t a, uint32_t b) {
  uint32_t r;
  asm("mul.rn.bf16x2 %0, %1, %2;" : "=r"(r) : "r"(a), "r"(b));
  return r;
}
__device__ __forceinline__ uint32_t bf2_fma(uint32_t a, uint32_t b, uint32_t c) {
  uint32_t r;
  asm("fma.rn.bf16x2 %0, %1, %2, %3;" : "=r"(r) : "r"(a), "r"(b), "r"(c));
  return r;
}
__device__ __forceinline__ uint32_t gelu_pack(float a0, float a1, uint32_t hbias2) {
  const uint32_t hp = bf2_fma(pack_bf16(a0, a1), 0x3f003f00u, hbias2);
  const uint32_t q = bf2_fma(bf2_mul(hp, hp), 0x3e923e92u  , 0x3fcc3fccu  );
  uint32_t t;
  asm("tanh.approx.bf16x2 %0, %1;" : "=r"(t) : "r"(bf2_mul(hp, q)));
  return bf2_fma(hp, t, hp);
}

#define R8(a, o) "+f"(a[o]), "+f"(a[o + 1]), "+f"(a[o + 2]), "+f"(a[o + 3]), "+f"(a[o + 4]), "+f"(a[o + 5]), "+f"(a[o + 6]), "+f"(a[o + 7])
#define W8(a, o) "=f"(a[o]), "=f"(a[o + 1]), "=f"(a[o + 2]), "=f"(a[o + 3]), "=f"(a[o + 4]), "=f"(a[o + 5]), "=f"(a[o + 6]), "=f"(a[o + 7])
#define REGS48 "{%0,%1,%2,%3,%4,%5,%6,%7,%8,%9,%10,%11,%12,%13,%14,%15,%16,%17,%18,%19,%20,%21,%22,%23," \
               "%24,%25,%26,%27,%28,%29,%30,%31,%32,%33,%34,%35,%36,%37,%38,%39,%40,%41,%42,%43,%44,%45,%46,%47}"
#define REGS32 "{%0,%1,%2,%3,%4,%5,%6,%7,%8,%9,%10,%11,%12,%13,%14,%15,%16,%17,%18,%19,%20,%21,%22,%23," \
               "%24,%25,%26,%27,%28,%29,%30,%31}"
#define DESC_HI_A  "0x40000040"
#define DESC_HI_B1 "0x80000020"
#define DESC_HI_B2 "0x40000040"
template <bool ACC, int OA, int OB>
__device__ __forceinline__ void wgmma_ss_n96(float (&d)[48], uint32_t da, uint32_t db) {
  if (ACC)
    asm volatile("{\n.reg .b64 xa, xb;\n.reg .b32 la, lb;\nadd.u32 la, %48, %50;\nadd.u32 lb, %49, %51;\n"
                 "mov.b64 xa, {la, " DESC_HI_A "};\nmov.b64 xb, {lb, " DESC_HI_B1 "};\n"
                 "wgmma.mma_async.sync.aligned.m64n96k16.f32.bf16.bf16 " REGS48 ", xa, xb, 1, 1, 1, 0, 1;\n}\n"
                 : R8(d, 0), R8(d, 8), R8(d, 16), R8(d, 24), R8(d, 32), R8(d, 40) : "r"(da), "r"(db), "n"(OA), "n"(OB));
  else
    asm volatile("{\n.reg .b64 xa, xb;\n.reg .b32 la, lb;\nadd.u32 la, %48, %50;\nadd.u32 lb, %49, %51;\n"
                 "mov.b64 xa, {la, " DESC_HI_A "};\nmov.b64 xb, {lb, " DESC_HI_B1 "};\n"
                 "wgmma.mma_async.sync.aligned.m64n96k16.f32.bf16.bf16 " REGS48 ", xa, xb, 0, 1, 1, 0, 1;\n}\n"
                 : W8(d, 0), W8(d, 8), W8(d, 16), W8(d, 24), W8(d, 32), W8(d, 40) : "r"(da), "r"(db), "n"(OA), "n"(OB));
}
template <bool ACC, int OB>
__device__ __forceinline__ void wgmma_rs_n64(float (&d)[32], uint32_t a0, uint32_t a1, uint32_t a2, uint32_t a3, uint32_t db) {
  if (ACC)
    asm volatile("{\n.reg .b64 xb;\n.reg .b32 lb;\nadd.u32 lb, %36, %37;\nmov.b64 xb, {lb, " DESC_HI_B2 "};\n"
                 "wgmma.mma_async.sync.aligned.m64n64k16.f32.bf16.bf16 " REGS32 ", {%32,%33,%34,%35}, xb, 1, 1, 1, 1;\n}\n"
                 : R8(d, 0), R8(d, 8), R8(d, 16), R8(d, 24) : "r"(a0), "r"(a1), "r"(a2), "r"(a3), "r"(db), "n"(OB));
  else
    asm volatile("{\n.reg .b64 xb;\n.reg .b32 lb;\nadd.u32 lb, %36, %37;\nmov.b64 xb, {lb, " DESC_HI_B2 "};\n"
                 "wgmma.mma_async.sync.aligned.m64n64k16.f32.bf16.bf16 " REGS32 ", {%32,%33,%34,%35}, xb, 0, 1, 1, 1;\n}\n"
                 : W8(d, 0), W8(d, 8), W8(d, 16), W8(d, 24) : "r"(a0), "r"(a1), "r"(a2), "r"(a3), "r"(db), "n"(OB));
}
template <int N> __device__ __forceinline__ void fence_regs(float (&d)[N]) {
#pragma unroll
  for (int i = 0; i < N; i++) asm volatile("" : "+f"(d[i])::"memory");
}

constexpr int XS_BYTES = 9 * 16384;
constexpr int STAGE_BYTES = 12288;
constexpr int OFF_ST = XS_BYTES;
constexpr int OFF_B1 = OFF_ST + 6 * STAGE_BYTES;
constexpr int OFF_B2 = OFF_B1 + 1152;
constexpr int OFF_BAR = OFF_B2 + 1152;
constexpr int B_FULL = 0, B_X = 48  , B_RB = 120  , B_OWN = 152, B_FIN = 160, B_A8 = 168, B_OWN2 = 176,
              B_EMPTY = 184  , B_TS = 232  , B_TS8 = 264, B_TR = 272  , B_P1L = 296, B_P1R = 304, B_U = 312,
              B_U0 = 320, NBARS = 41,
              B_CONV = 328, B_COMB = 336;
constexpr int OFF_A8 = OFF_BAR + 512;
constexpr int OFF_ARGS = OFF_A8 + 2048;
constexpr int SMEM_BYTES = OFF_ARGS + 256 + 1024;
constexpr int OFF_STG = 65536, OFF_C8 = 131072;
constexpr int E_UA = 0, E_UB = 3616, E_W3A = 7232, E_W3B = 10848, E_W5 = 14464, E_W9 = 17568, E_TAP = 19680, E_SIZE = 23392;
constexpr int L_W7 = 4752, L_KB = 6832, L_Y = 6848, L_YB = 8304, L_SIZE = 28656;
constexpr int L_CONST = L_Y, L_KC = L_Y + 10240;
constexpr int TP_0 = 0, TP_W3A = 580, TP_UA = 716, TP_UB = 852, TP_W3B = 988, TP_W5 = 1248, TP_W9 = 1448, TP_W7 = 1648,
              TP_COPY = 1856;
__device__ __forceinline__ int e_off(int ch) { return ch == 0 ? 0 : OFF_ST + (ch - 1) * E_SIZE; }
__device__ __forceinline__ int l_off(int ch) { return 32768 + ch * L_SIZE; }
__device__ __forceinline__ int xg_off(int box) { return box < 4 ? OFF_ST + box * 4096 : 170880 + (box - 4) * 4096; }

__device__ __forceinline__ void ln_load(const __nv_bfloat16* __restrict__ x, const __nv_bfloat16* __restrict__ gate_w,
                                        int row, int lane, uint32_t (&w)[9], uint32_t (&gw)[9]) {
  const uint32_t* xr = reinterpret_cast<const uint32_t*>(x + (size_t)row * D_MOD) + lane;
  const uint32_t* gwp = reinterpret_cast<const uint32_t*>(gate_w) + lane;
#pragma unroll
  for (int j = 0; j < 9; j++) {
    asm volatile("ld.global.nc.u32 %0, [%1];" : "=r"(w[j]) : "l"(xr + j * 32));
    asm volatile("ld.global.nc.u32 %0, [%1];" : "=r"(gw[j]) : "l"(gwp + j * 32));
  }
}
__device__ __forceinline__ void ln_row(int row, int lane, const Scratch& sc, const uint32_t (&w)[9], const uint32_t (&gw)[9]) {
  float s = 0.f, gsum = 0.f;
#pragma unroll
  for (int j = 0; j < 9; j++) {
    uint32_t pr2 = bf2_mul(w[j], gw[j]);
    s += bf_lo(w[j]) + bf_hi(w[j]);
    gsum += bf_lo(pr2) + bf_hi(pr2);
  }
#pragma unroll
  for (int o = 1; o < 32; o <<= 1) { s += __shfl_xor_sync(~0u, s, o); gsum += __shfl_xor_sync(~0u, gsum, o); }
  const float mean = s * (1.0f / 576.0f);
  float vs = 0.f;
#pragma unroll
  for (int j = 0; j < 9; j++) {
    float d0 = bf_lo(w[j]) - mean, d1 = bf_hi(w[j]) - mean;
    vs = fmaf(d0, d0, vs); vs = fmaf(d1, d1, vs);
  }
#pragma unroll
  for (int o = 1; o < 32; o <<= 1) vs += __shfl_xor_sync(~0u, vs, o);
  const float mb = bf_round(mean);
  const float vb = bf_round(vs * (1.0f / 576.0f));
  const float rinv = __frcp_rn(bf_round(__fsqrt_rn(bf_round(vb + 1e-5f))));
  const uint32_t nm2 = pack_bf16(-mb, -mb);
  uint32_t* dst = reinterpret_cast<uint32_t*>(sc.xn + (size_t)row * D_MOD) + lane;
#pragma unroll
  for (int j = 0; j < 9; j++) {
    uint32_t dd = bf2_add(w[j], nm2);
    dst[j * 32] = pack_bf16(bf_lo(dd) * rinv, bf_hi(dd) * rinv);
  }
  if (lane == 0) {
    float gv = bf_round(__fdividef(1.0f, 1.0f + __expf(-bf_round(gsum))));
    float og = bf_round(1.0f - gv);
    sc.gate[row] = make_uint2(pack_bf16(gv, gv), pack_bf16(og, og));
  }
}
__device__ __forceinline__ void mma_bf16(float (&d)[4], uint32_t a0, uint32_t a1, uint32_t a2, uint32_t a3, uint32_t b0, uint32_t b1) {
  asm("mma.sync.aligned.m16n8k16.row.col.f32.bf16.bf16.f32 {%0,%1,%2,%3}, {%4,%5,%6,%7}, {%8,%9}, {%0,%1,%2,%3};"
      : "+f"(d[0]), "+f"(d[1]), "+f"(d[2]), "+f"(d[3]) : "r"(a0), "r"(a1), "r"(a2), "r"(a3), "r"(b0), "r"(b1));
}
__device__ __forceinline__ void mma_tf32(float (&d)[4], float a0, float a1, float a2, float a3, float b0, float b1) {
  asm("mma.sync.aligned.m16n8k8.row.col.f32.tf32.tf32.f32 {%0,%1,%2,%3}, {%4,%5,%6,%7}, {%8,%9}, {%0,%1,%2,%3};"
      : "+f"(d[0]), "+f"(d[1]), "+f"(d[2]), "+f"(d[3])
      : "r"(__float_as_uint(a0)), "r"(__float_as_uint(a1)), "r"(__float_as_uint(a2)), "r"(__float_as_uint(a3)),
        "r"(__float_as_uint(b0)), "r"(__float_as_uint(b1)));
}
__device__ __forceinline__ float2 cexp_l(float al, float th, float l) {
  float mg;
  asm("ex2.approx.ftz.f32 %0, %1;" : "=f"(mg) : "f"(al * l));
  const float tr = th * l;
  return make_float2(mg * __cosf(tr), mg * __sinf(tr));
}
__device__ __forceinline__ float2 cmul(float2 a, float2 b) {
  return make_float2(fmaf(a.x, b.x, -a.y * b.y), fmaf(a.x, b.y, a.y * b.x));
}
__device__ __forceinline__ float2 cmulc(float2 a, float2 b) {
  return make_float2(fmaf(a.x, b.x, -a.y * b.y), fmaf(-a.x, b.y, -a.y * b.x));
}
__device__ __forceinline__ float2 csq(float2 a) { return make_float2(fmaf(a.x, a.x, -a.y * a.y), 2.0f * a.x * a.y); }
#define SM_U32(p) (*reinterpret_cast<uint32_t*>(p))
#define SM_F32(p) (*reinterpret_cast<float*>(p))
#define SM_U16(p) (*reinterpret_cast<unsigned short*>(p))
#define SM_U2(p) (*reinterpret_cast<uint2*>(p))
#define SM_F2(p) (*reinterpret_cast<float2*>(p))
#define SM_U4(p) (*reinterpret_cast<uint4*>(p))
#define SM_F4(p) (*reinterpret_cast<float4*>(p))
template <int OFF, int TAG>
__device__ __forceinline__ uint32_t lds_free(uint32_t base) {
  uint32_t v;
  asm volatile("ld.volatile.shared.u32 %0, [%1+%2]; // %3" : "=r"(v) : "r"(base), "n"(OFF), "n"(TAG));
  return v;
}
template <int K0, int K1, int OFF, int K>
__device__ __forceinline__ void load_tquads_(uint32_t (&q)[K1 - K0][4], uint32_t tp) {
  if constexpr (K >= K0) {
    q[K - K0][0] = lds_free<OFF - 32 * K, 0>(tp);
    q[K - K0][1] = lds_free<OFF - 32 * K - 16, 1>(tp);
    q[K - K0][2] = lds_free<OFF - 32 * K + 16, 2>(tp);
    q[K - K0][3] = lds_free<OFF - 32 * K, 3>(tp);
    load_tquads_<K0, K1, OFF, K - 1>(q, tp);
  }
}
template <int K0, int K1, int OFF>
__device__ __forceinline__ void load_tquads(uint32_t (&q)[K1 - K0][4], uint32_t tp) {
  load_tquads_<K0, K1, OFF, K1 - 1>(q, tp);
}
__device__ __forceinline__ void ldsm4_free(uint32_t (&r)[4], uint32_t addr) {
  asm("ldmatrix.sync.aligned.m8n8.x4.shared.b16 {%0,%1,%2,%3}, [%4];"
      : "=r"(r[0]), "=r"(r[1]), "=r"(r[2]), "=r"(r[3]) : "r"(addr));
}
__device__ __forceinline__ void ldsm4t_free(uint32_t (&r)[4], uint32_t addr) {
  asm("ldmatrix.sync.aligned.m8n8.x4.trans.shared.b16 {%0,%1,%2,%3}, [%4];"
      : "=r"(r[0]), "=r"(r[1]), "=r"(r[2]), "=r"(r[3]) : "r"(addr));
}
__device__ __forceinline__ uint32_t ldg_u16(const __nv_bfloat16* p) {
  unsigned short v;
  asm volatile("ld.global.nc.u16 %0, [%1];" : "=h"(v) : "l"(p));
  return v;
}
__device__ __forceinline__ void ldsm4t(uint32_t (&r)[4], uint32_t addr) {
  asm volatile("ldmatrix.sync.aligned.m8n8.x4.trans.shared.b16 {%0,%1,%2,%3}, [%4];"
               : "=r"(r[0]), "=r"(r[1]), "=r"(r[2]), "=r"(r[3]) : "r"(addr) : "memory");
}
template <int I0, int I1, int K0, int K1, int JMIN, int RB, int TOFF>
__device__ __forceinline__ void band(float (&acc)[I1 - I0][4], uint32_t tp, uint32_t sa, uint32_t za, int lane) {
  uint32_t tq[K1 - K0][4];
  load_tquads<K0, K1, TOFF>(tq, tp);
  constexpr int JL = (I0 - K1 + 1 > JMIN) ? I0 - K1 + 1 : JMIN, JH = I1 - 1 - K0;
  constexpr int JP = (JL >= 0) ? (JL & ~1) : -2;
#pragma unroll
  for (int J2 = JP; J2 <= JH; J2 += 2) {
    uint32_t b[4];
    ldsm4t_free(b, (J2 < 0 && lane < 31) ? za : sa + J2 * 16 * RB);
#pragma unroll
    for (int hf = 0; hf < 2; hf++) {
      const int J = J2 + hf;
#pragma unroll
      for (int k = K0; k < K1; k++) {
        const int I = J + k;
        if (J >= JL && J <= JH && I >= I0 && I < I1)
          mma_bf16(acc[I - I0], tq[k - K0][0], tq[k - K0][1], tq[k - K0][2], tq[k - K0][3], b[2 * hf], b[2 * hf + 1]);
      }
    }
  }
}
template <int I0, int I1>
__device__ __forceinline__ void p8_tiles(uint32_t ea, uint32_t za, char* lb, uint32_t tp, int lane) {
  float acc[I1 - I0][4];
#pragma unroll
  for (int i = 0; i < I1 - I0; i++) { acc[i][0] = acc[i][1] = acc[i][2] = acc[i][3] = 0.f; }
  const uint32_t sa = ea + 32 + lane * 16;
  band<I0, I1, 2, 5, -1, 16, TP_W3A + 160>(acc, tp, sa + E_W3A, za, lane);
  band<I0, I1, 2, 5, 0, 16, TP_UA + 160>(acc, tp, sa + E_UA, za, lane);
  band<I0, I1, 2, 5, 0, 16, TP_UB + 160>(acc, tp, sa + E_UB, za, lane);
  band<I0, I1, 2, 9, 0, 16, TP_W3B + 288>(acc, tp, sa + E_W3B, za, lane);
  band<I0, I1, 4, 9, -1, 16, TP_W5 + 288>(acc, tp, sa + E_W5, za, lane);
  char* a = lb + L_Y + L_YB + 4 * (8 * (lane >> 2) + 2 * (lane & 3));
#pragma unroll
  for (int I = I0; I < I1; I++) {
    SM_F2(a + 4 * (128 * I + 4 * (I >> 1))) = make_float2(acc[I - I0][0], acc[I - I0][1]);
    SM_F2(a + 4 * (128 * I + 4 * (I >> 1)) + 256) = make_float2(acc[I - I0][2], acc[I - I0][3]);
  }
}

struct MlpCtx {
  uint32_t bars;
  uint32_t dA, dB;
  int lane;
};
__device__ __forceinline__ void stage_release(const MlpCtx& c, int slot) {
  if (c.lane == 0) mbar_arrive(c.bars + B_EMPTY + 8 * slot);
}
template <int P>
__device__ __forceinline__ void gelu_part(uint32_t baddr, float (&acc)[48]) {
  asm volatile("" : R8(acc, P * 8)::"memory");
  const uint32_t b0 = bf2_mul(lds32(baddr + P * 32), 0x3f003f00u), b1 = bf2_mul(lds32(baddr + P * 32 + 16), 0x3f003f00u);
  uint32_t r0 = gelu_pack(acc[P * 8 + 0], acc[P * 8 + 1], b0);
  uint32_t r1 = gelu_pack(acc[P * 8 + 2], acc[P * 8 + 3], b0);
  uint32_t r2 = gelu_pack(acc[P * 8 + 4], acc[P * 8 + 5], b1);
  uint32_t r3 = gelu_pack(acc[P * 8 + 6], acc[P * 8 + 7], b1);
  acc[P * 8 + 0] = __uint_as_float(r0);
  acc[P * 8 + 1] = __uint_as_float(r1);
  acc[P * 8 + 2] = __uint_as_float(r2);
  acc[P * 8 + 3] = __uint_as_float(r3);
}
__device__ __forceinline__ void h_push(uint32_t (&h)[144], float (&acc)[48]) {
  asm volatile("" : R8(acc, 0)::"memory");
#pragma unroll
  for (int i = 0; i < 96; i++) h[i] = h[i + 24];
#pragma unroll
  for (int i = 0; i < 24; i++) h[96 + i] = __float_as_uint(acc[(i >> 2) * 8 + (i & 3)]);
}
template <int SB, int I>
__device__ __forceinline__ void p1_mma(const MlpCtx& c, float (&cur)[48]) {
  constexpr int S = SB % 9;
  wgmma_ss_n96<(S | I) != 0, ((S * 16384 + I * 32) >> 4),
               (4096 >> 4 << 16) + (((SB % 6) * STAGE_BYTES + I * 1024) >> 4)>(cur, c.dA, c.dB);
}
template <int SB>
__device__ __forceinline__ void p1_stage(const MlpCtx& c, int j, uint32_t baddr, float (&cur)[48], float (&prev)[48],
                                         uint32_t (&h)[144]) {
  constexpr int S = SB % 9;
  if (SB < 9) mbar_wait(c.bars + B_X + 8 * S, 0);
  mbar_wait(c.bars + B_FULL + 8 * (SB % 6), ((SB / 6) + j) & 1);
  WG_FENCE();
  p1_mma<SB, 0>(c, cur); p1_mma<SB, 1>(c, cur); p1_mma<SB, 2>(c, cur); p1_mma<SB, 3>(c, cur);
  WG_COMMIT();
  if (S >= 1 && S <= 6) gelu_part<(S >= 1 && S <= 6) ? S - 1 : 0>(baddr, prev);
  if (S == 7) h_push(h, prev);
  wg_wait<1>();
  if (SB > 0 || j > 0) stage_release(c, (SB + 5) % 6);
  if (S == 0) fence_regs(prev);
}
template <int SB0>
__device__ __forceinline__ void p1_chunk(const MlpCtx& c, int j, uint32_t baddr, float (&cur)[48], float (&prev)[48],
                                         uint32_t (&h)[144]) {
  p1_stage<SB0 + 0>(c, j, baddr, cur, prev, h); p1_stage<SB0 + 1>(c, j, baddr, cur, prev, h);
  p1_stage<SB0 + 2>(c, j, baddr, cur, prev, h); p1_stage<SB0 + 3>(c, j, baddr, cur, prev, h);
  p1_stage<SB0 + 4>(c, j, baddr, cur, prev, h); p1_stage<SB0 + 5>(c, j, baddr, cur, prev, h);
  p1_stage<SB0 + 6>(c, j, baddr, cur, prev, h); p1_stage<SB0 + 7>(c, j, baddr, cur, prev, h);
  p1_stage<SB0 + 8>(c, j, baddr, cur, prev, h);
}
template <int S, int I>
__device__ __forceinline__ void p2_one(const MlpCtx& c, float (&cur)[32], uint32_t (&h)[144]) {
  constexpr int kk = 6 * S + I;
  wgmma_rs_n64<(S | I) != 0, ((S * STAGE_BYTES + I * 2048) >> 4)>(cur, h[4 * kk], h[4 * kk + 1], h[4 * kk + 2], h[4 * kk + 3], c.dB);
}
template <int S>
__device__ __forceinline__ void p2_mma(const MlpCtx& c, uint32_t parity, float (&cur)[32], uint32_t (&h)[144]) {
  mbar_wait(c.bars + B_FULL + 8 * S, parity);
  WG_FENCE();
  p2_one<S, 0>(c, cur, h); p2_one<S, 1>(c, cur, h); p2_one<S, 2>(c, cur, h);
  p2_one<S, 3>(c, cur, h); p2_one<S, 4>(c, cur, h); p2_one<S, 5>(c, cur, h);
  WG_COMMIT();
}
__device__ __forceinline__ int chunk_of(int pos, int pr, int rank) {
  const int off = (int)(0x03231201ull >> (4 * pos)) & 3;
  const int mine = (0x168 >> pos) & 1;
  return pos == 1 ? 8 : 2 * ((pr + off) & 3) + (mine ? rank : rank ^ 1);
}
__device__ __forceinline__ void bulk_s2peer(uint32_t rdst, uint32_t src, uint32_t bytes, uint32_t rbar) {
  asm volatile("cp.async.bulk.shared::cluster.shared::cta.mbarrier::complete_tx::bytes [%0], [%1], %2, [%3];"
               ::"r"(rdst), "r"(src), "r"(bytes), "r"(rbar) : "memory");
}
__device__ __forceinline__ void bulk_s2g_release(void* gdst, uint32_t src, uint32_t bytes) {
  asm volatile("cp.async.bulk.global.shared::cta.bulk_group [%0], [%1], %2;\n"
               "cp.async.bulk.commit_group;\ncp.async.bulk.wait_group 0;\nfence.acq_rel.gpu;"
               ::"l"(gdst), "r"(src), "r"(bytes) : "memory");
}
struct Args {
  const __nv_bfloat16 *u, *Are, *Aim, *Bre, *Bim, *Cre, *Cim, *logdt, *Dskip, *gate_w, *w1, *w2, *b1, *b2;
  __nv_bfloat16* out;
};

struct Maps { const CUtensorMap *x, *w1, *xn; };
__device__ __forceinline__ void load_params(uint32_t (&v)[8], const Args& ar, int d, int n) {
  const int idx = d * N_ST + n;
  v[0] = ldg_u16(ar.Are + idx); v[1] = ldg_u16(ar.Aim + idx); v[2] = ldg_u16(ar.Bre + idx); v[3] = ldg_u16(ar.Bim + idx);
  v[4] = ldg_u16(ar.Cre + idx); v[5] = ldg_u16(ar.Cim + idx); v[6] = ldg_u16(ar.logdt + d); v[7] = ldg_u16(ar.Dskip + d);
}
__device__ __forceinline__ uint4 pack_params(uint32_t (&v)[8]) {
  asm volatile("" : "+r"(v[0]), "+r"(v[1]), "+r"(v[2]), "+r"(v[3]), "+r"(v[4]), "+r"(v[5]), "+r"(v[6]), "+r"(v[7])::"memory");
  return make_uint4(v[0] | (v[1] << 16), v[2] | (v[3] << 16), v[4] | (v[5] << 16), v[6] | (v[7] << 16));
}
__device__ __noinline__ uint4 ssm_pass(const Maps tm, char* sm, const int d0, const int pass, const uint4 pv
) {
  const Args& ar = *reinterpret_cast<const Args*>(sm + OFF_ARGS);
  const Scratch& sc = *reinterpret_cast<const Scratch*>(sm + OFF_ARGS + 128);
  const uint32_t sb = smem_u32(sm), bars = sb + OFF_BAR;
  const int tid = threadIdx.x, lane = tid & 31;
  const int warp = __shfl_sync(0xffffffffu, tid >> 5, 0);
  const int bid = blockIdx.x, m = bid >> 3, f = bid & 7;
  const int g = lane >> 2, cc = lane & 3;
  const int ch = warp >> 2, n = tid & 127;
  char* eb = sm + e_off(ch);
  char* lb = sm + l_off(ch);
#define CH_SYNC() asm volatile("bar.sync %0, 128;" ::"r"(ch + 1) : "memory")
  const bool lead = warp < 8;
  {
    const float are = bf_lo(pv.x), aim = bf_hi(pv.x), bre = bf_lo(pv.y), bim = bf_hi(pv.y);
    const float cre = bf_lo(pv.z), cim = bf_hi(pv.z), ldt = bf_lo(pv.w), dsk = bf_hi(pv.w);
    const float dt = bf_round(expf(ldt));
    const float al = (dt * are) * 1.4426950408889634f, th = dt * aim;
    constexpr float TF32_UNBIAS = 1.0f + 0.7f / 1024.0f;
    const float2 c0 = cmul(make_float2(cre * TF32_UNBIAS, cim * TF32_UNBIAS), make_float2(dt * bre, dt * bim));
    const float2 e64 = cexp_l(al, th, 64.f), e128 = csq(e64), e256 = cexp_l(al, th, 256.f), e512 = csq(e256);
    const float2 k128 = cmul(c0, e128), k256 = cmul(c0, e256), k384 = cmul(k256, e128);
    const float2 k512 = cmul(c0, e512), k516 = cmul(k512, cexp_l(al, th, 4.f));
    const float2 e1024 = cexp_l(al, th, 1024.f), k1024 = cmul(c0, e1024);
    float k2048 = fmaf(k1024.x, e1024.x, -k1024.y * e1024.y) * (1.0f / TF32_UNBIAS);
    char* ca = lb + L_CONST + n * 80;
    SM_F4(ca) = make_float4(al, th, e64.x, e64.y);
    SM_F4(ca + 16) = make_float4(c0.x, c0.y, k128.x, k128.y);
    SM_F4(ca + 32) = make_float4(k256.x, k256.y, k384.x, k384.y);
    SM_F4(ca + 48) = make_float4(k512.x, k512.y, k516.x, k516.y);
    SM_F2(ca + 64) = k1024;
#pragma unroll
    for (int o = 16; o > 0; o >>= 1) k2048 += __shfl_xor_sync(~0u, k2048, o);
    if (lane == 0) SM_F32(lb + L_KC + (warp & 3) * 2576 + 2560) = k2048;
    if (n == 0) SM_F32(lb + L_KB + 8) = dsk;
    __syncwarp();
    DBG_S(0);
    float kd[5][4];
#pragma unroll
    for (int t = 0; t < 5; t++) { kd[t][0] = kd[t][1] = kd[t][2] = kd[t][3] = 0.f; }
    const float l1 = (float)g, l128 = (float)(128 * g);
    const char* cr = lb + L_CONST + ((warp & 3) * 32 + cc) * 80;
    const int o2 = 32 + (g >> 2) * 8, o3 = 48 + (g & 1) * 8, s2 = ((g & 3) << 2) | cc, s3 = ((g >> 1) << 2) | cc;
#pragma unroll 2
    for (int st = 0; st < 8; st++, cr += 320) {
      const float4 q0 = *(const float4*)cr, q1 = *(const float4*)(cr + 16);
      const float2 q2 = *(const float2*)(cr + o2), q3 = *(const float2*)(cr + o3), q4 = *(const float2*)(cr + 64);
      const float2 p1 = cexp_l(q0.x, q0.y, l1), p128 = cexp_l(q0.x, q0.y, l128);
      const float2 p2 = csq(p1), p8 = csq(csq(p2));
      const float2 a1 = cmul(p8, make_float2(q0.z, q0.w));
      float2 x = cmulc(make_float2(q1.x, q1.y), p1);
      mma_tf32(kd[0], p8.x, a1.x, p8.y, a1.y, x.x, x.y);
      x = cmulc(make_float2(q1.z, q1.w), p1);
      mma_tf32(kd[1], p8.x, a1.x, p8.y, a1.y, x.x, x.y);
      x = cmulc(q2, make_float2(__shfl_sync(~0u, p2.x, s2), __shfl_sync(~0u, p2.y, s2)));
      mma_tf32(kd[2], p8.x, a1.x, p8.y, a1.y, x.x, x.y);
      x = cmulc(q3, make_float2(__shfl_sync(~0u, p128.x, s3), __shfl_sync(~0u, p128.y, s3)));
      mma_tf32(kd[3], p8.x, a1.x, p8.y, a1.y, x.x, x.y);
      x = cmulc(q4, p128);
      mma_tf32(kd[4], p8.x, a1.x, p8.y, a1.y, x.x, x.y);
    }
    char* kc = lb + L_KC + (warp & 3) * 2576;
#pragma unroll
    for (int e = 0; e < 2; e++) {
      const int row = g + e * 8;
      SM_F2(kc + 4 * (8 * row + 2 * cc)) = make_float2(kd[0][2 * e], kd[0][2 * e + 1]);
      SM_F2(kc + 4 * (128 + 8 * row + 2 * cc)) = make_float2(kd[1][2 * e], kd[1][2 * e + 1]);
      SM_F2(kc + 4 * (256 + 64 * (cc >> 1) + 4 * row + 2 * (cc & 1))) = make_float2(kd[2][2 * e], kd[2][2 * e + 1]);
      SM_F2(kc + 4 * (384 + 32 * cc + 2 * row)) = make_float2(kd[3][2 * e], kd[3][2 * e + 1]);
      SM_F32(kc + 4 * (512 + 32 * cc + row)) = kd[4][2 * e];
      SM_F32(kc + 4 * (528 + 32 * cc + row)) = kd[4][2 * e + 1];
    }
  }
  DBG_S(1);
  CH_SYNC();
  {
    const char* kc = lb + L_KC;
    auto kq = [&](int idx) {
      const char* q = kc + 4 * idx;
      return (*(const float*)q + *(const float*)(q + 2576)) + (*(const float*)(q + 5152) + *(const float*)(q + 7728));
    };
#pragma unroll
    for (int it = 0; it < 5; it++) {
      const int idx = n + 128 * it;
      float t = kq(idx);
      if ((it == 1 || it == 2) && n == 127) t -= kq(idx + 1);
      if (it == 4 && n == 0) { SM_F2(lb + L_KB) = make_float2(t, kq(640)); t = 0.f; }
      int off;
      if (it < 2) off = TP_0 + 2 * (272 - idx);
      else if (it == 2) {
        const int sel = n & 3, mu = 32 + (n >> 2);
        off = sel == 2 ? TP_W3B + 2 * (144 - mu) : (sel == 0 ? TP_W3A : sel == 1 ? TP_UA : TP_UB) + 2 * (80 - mu);
      } else if (it == 3) off = ((n & 1) ? TP_W3B : TP_W5) + 2 * (80 - (n >> 1));
      else off = ((n & 1) ? TP_W7 : TP_W9) + 2 * (80 - (n >> 1));
      const unsigned short hv = pack_bf16(t, 0.f);
      SM_U16(eb + E_TAP + off) = hv;
      SM_U16(eb + E_TAP + TP_COPY + off + 2) = hv;
    }
  }
  DBG_S(2);
  if (!lead && bid < 128) {
    uint32_t lw[9], lx[9], lg[9];
    const int row = bid * 16 + (warp - 8) * 2;
    ln_load(ar.u, ar.gate_w, row, lane, lw, lg);
    ln_load(ar.u, ar.gate_w, row + 1, lane, lx, lg);
    ln_row(row, lane, sc, lw, lg);
    ln_row(row + 1, lane, sc, lx, lg);
    asm volatile("bar.sync 5, 256;" ::: "memory");
  }
  if (lead) {
    mbar_wait(bars + B_U, pass & 1);
    if (pass > 0) mbar_wait(bars + B_COMB, (pass - 1) & 1);
    const uint32_t src = sb + xg_off(warp) + lane * 16;
    const int mych = g - (d0 & 4);
    char* dst = sm + l_off(mych) + (warp + 1) * 528 + cc * 4;
#pragma unroll
    for (int i = 0; i < 8; i++) {
      uint32_t r[4];
      ldsm4t(r, src + i * 512);
      if (mych >= 0 && mych < 4) {
#pragma unroll
        for (int k = 0; k < 4; k++) SM_U32(dst + i * 64 + k * 16) = r[k];
      }
    }
    __syncwarp();
    if (lane == 0) mbar_arrive(bars + B_U0);
    if (bid < 128 && tid == 0) {
      asm volatile("cp.async.bulk.prefetch.L2.global [%0], %1;" ::"l"(ar.w1 + (size_t)bid * 20736), "r"(41472) : "memory");
      asm volatile("cp.async.bulk.prefetch.L2.global [%0], %1;" ::"l"(ar.w2 + (size_t)bid * 20736), "r"(41472) : "memory");
    }
  }
  DBG_S(3);
  mbar_wait(bars + B_U0, pass & 1);
  DBG_S(4);
#pragma unroll 1
  for (int i = n - 1; i < 224; i += 128) {
    const char* ur = lb + ((i >> 5) + 1) * 528 + (i & 31) * 16;
    const uint4 w0 = *(const uint4*)(ur - ((i & 31) ? 16 : 32) + (i < 0 ? 16 : 0)), w1 = *(const uint4*)ur,
                w2 = *(const uint4*)(ur + ((i & 31) == 31 ? 32 : 16));
    const uint32_t wv[12] = {w0.x, w0.y, w0.z, w0.w, w1.x, w1.y, w1.z, w1.w, w2.x, w2.y, w2.z, w2.w};
    char* o = eb + 32 + 16 * i;
    SM_U4(o + E_UA) = make_uint4(wv[3], wv[4], wv[5], wv[6]);
    SM_U4(o + E_UB) = make_uint4(wv[1], wv[2], wv[3], wv[4]);
    float v[22], wa[16];
#pragma unroll
    for (int k = 1; k < 11; k++) { v[2 * k] = bf_lo(wv[k]); v[2 * k + 1] = bf_hi(wv[k]); }
#pragma unroll
    for (int k = 4; k < 16; k++) wa[k] = (v[k - 1] + v[k]) + v[k + 1];
    SM_U4(o + E_W3A) = make_uint4(pack_bf16(wa[8], wa[9]), pack_bf16(wa[10], wa[11]), pack_bf16(wa[12], wa[13]), pack_bf16(wa[14], wa[15]));
    SM_U4(o + E_W3B) = make_uint4(pack_bf16(wa[4], wa[5]), pack_bf16(wa[6], wa[7]), pack_bf16(wa[8], wa[9]), pack_bf16(wa[10], wa[11]));
    if (i < 192) {
#pragma unroll
      for (int k = 8; k < 16; k++) wa[k] += v[k - 2] + v[k + 2];
      SM_U4(o + E_W5) = make_uint4(pack_bf16(wa[8], wa[9]), pack_bf16(wa[10], wa[11]), pack_bf16(wa[12], wa[13]), pack_bf16(wa[14], wa[15]));
      if (i < 128) {
#pragma unroll
        for (int k = 8; k < 16; k++) wa[k] += v[k - 3] + v[k + 3];
        SM_U4(lb + L_W7 + 32 + 16 * i) =
            make_uint4(pack_bf16(wa[8], wa[9]), pack_bf16(wa[10], wa[11]), pack_bf16(wa[12], wa[13]), pack_bf16(wa[14], wa[15]));
#pragma unroll
        for (int k = 8; k < 16; k++) wa[k] += v[k - 4] + v[k + 4];
        SM_U4(o + E_W9) = make_uint4(pack_bf16(wa[8], wa[9]), pack_bf16(wa[10], wa[11]), pack_bf16(wa[12], wa[13]), pack_bf16(wa[14], wa[15]));
      }
    }
  }
  if (bid < 128 && tid == 480) {
    asm volatile("fence.acq_rel.gpu;" ::: "memory");
    atomicAdd(&sc.flags[256 + m], 1u);
  }
  __syncwarp();
  CH_SYNC();
  DBG_S(5);
  {
    const int role = (warp + ch) & 3;
    uint32_t ea = smem_u32(eb), za = smem_u32(lb);
    asm volatile("" : "+r"(ea), "+r"(za)::"memory");
    const uint32_t tp = ea + E_TAP + ((g & 1) ? TP_COPY + 2 : 0) - 2 * (g - 2 * cc);
    if (role < 2) {
      uint32_t ta[17][4];
      load_tquads<0, 17, TP_0 + 544>(ta, tp);
      float acc[8][4];
#pragma unroll
      for (int i = 0; i < 8; i++) { acc[i][0] = acc[i][1] = acc[i][2] = acc[i][3] = 0.f; }
      const uint32_t bpos = za + ((lane & 7) + 1) * 528 + role * 256 + (lane >> 3) * 16;
      const uint32_t bmid = role ? bpos : bpos - 16;
#pragma unroll
      for (int j2 = -16; j2 < 8; j2 += 2) {
        uint32_t b[4];
        ldsm4_free(b, (j2 < -8 ? bpos - 16 : j2 < 0 ? bmid : bpos) + 32 * j2);
#pragma unroll
        for (int hf = 0; hf < 2; hf++) {
#pragma unroll
          for (int i = 0; i < 8; i++) {
            const int k = i - j2 - hf;
            if (k >= 0 && k <= 16) mma_bf16(acc[i], ta[k][0], ta[k][1], ta[k][2], ta[k][3], b[2 * hf], b[2 * hf + 1]);
          }
        }
      }
      char* ya = lb + L_Y + 4 * (520 * cc + 128 * role + g);
#pragma unroll
      for (int i = 0; i < 8; i++) {
        SM_F32(ya + 64 * i) = acc[i][0]; SM_F32(ya + 64 * i + 1040) = acc[i][1];
        SM_F32(ya + 64 * i + 32) = acc[i][2]; SM_F32(ya + 64 * i + 1072) = acc[i][3];
      }
    } else if (role == 2) {
      p8_tiles<1, 11>(ea, za, lb, tp, lane);
    } else {
      p8_tiles<11, 16>(ea, za, lb, tp, lane);
      float acc[2][5][4];
#pragma unroll
      for (int i = 0; i < 10; i++) { acc[i / 5][i % 5][0] = acc[i / 5][i % 5][1] = acc[i / 5][i % 5][2] = acc[i / 5][i % 5][3] = 0.f; }
#pragma unroll
      for (int sg = 0; sg < 2; sg++) {
        uint32_t tq[5][4];
        if (sg == 0) load_tquads<4, 9, TP_W9 + 288>(tq, tp); else load_tquads<4, 9, TP_W7 + 288>(tq, tp);
        const uint32_t sa = (sg == 0 ? ea + E_W9 : za + L_W7 - 16) + 32 + (lane & 15) * 32 + (lane >> 4) * 16;
#pragma unroll
        for (int J = -1 + sg; J < 4; J++) {
          uint32_t b[4];
          ldsm4t_free(b, (J < 0 && (lane & 15) < 15) ? za : sa + J * 512);
#pragma unroll
          for (int k = 4; k < 9; k++) {
            const int I = J + k;
            if (I < 8) {
              mma_bf16(acc[0][I - 3], tq[k - 4][0], tq[k - 4][1], tq[k - 4][2], tq[k - 4][3], b[0], b[1]);
              mma_bf16(acc[1][I - 3], tq[k - 4][0], tq[k - 4][1], tq[k - 4][2], tq[k - 4][3], b[2], b[3]);
            }
          }
        }
      }
      char* a = lb + L_Y + 2 * L_YB + 4 * (16 * g + 2 * cc);
#pragma unroll
      for (int hh = 0; hh < 2; hh++) {
#pragma unroll
        for (int I = 3; I < 8; I++) {
          SM_F2(a + 32 * hh + 1040 * (I - 3)) = make_float2(acc[hh][I - 3][0], acc[hh][I - 3][1]);
          SM_F2(a + 32 * hh + 1040 * (I - 3) + 512) = make_float2(acc[hh][I - 3][2], acc[hh][I - 3][3]);
        }
      }
    }
  }
  __syncwarp();
  if (lane == 0) {
    mbar_arrive(bars + B_CONV);
    if (!lead) {
      const int iw = warp - 8;
      mbar_wait(bars + B_CONV, pass & 1);
      HFENCE();
      if (bid >= 128) {
        if (pass < 3) {
          mbar_expect_tx(bars + B_U, 4096);
          tma2d(sb + xg_off(iw), tm.x, (d0 + 4) & ~7, iw * 256, bars + B_U);
        }
      } else if (iw < 6) {
        mbar_expect_tx(bars + B_FULL + 8 * iw, STAGE_BYTES);
        tma3d(sb + OFF_ST + iw * STAGE_BYTES, tm.w1, 0, iw * 64, f * 18, bars + B_FULL + 8 * iw);
      } else {
        wait_flag(&sc.flags[256 + m], 8);
        mbar_expect_tx(bars + B_X + 8 * (iw - 6), 16384);
        tma2d(sb + (iw - 6) * 16384, tm.xn, (iw - 6) * 64, m * 128, bars + B_X + 8 * (iw - 6));
      }
    }
  }
  __syncwarp();
  CH_SYNC();
  DBG_S(6);
  uint32_t pnext[8];
#pragma unroll
  for (int i = 0; i < 8; i++) pnext[i] = 0;
  if (bid >= 128 && pass < 3) load_params(pnext, ar, d0 + 4 + ch, n);
  {
    const float4 kb = SM_F4(lb + L_KB);
    const uint32_t dk = pack_bf16(kb.z, kb.z);
#pragma unroll
    for (int k = 0; k < 4; k++) {
      const int t0 = n * 4 + 512 * k;
      char* ya = lb + L_Y + 4 * (t0 + 4 * (t0 >> 8));
      float4 y = SM_F4(ya);
      if (k > 0 || t0 >= 128) { const float4 b = SM_F4(ya + L_YB); y.x += b.x; y.y += b.y; y.z += b.z; y.w += b.w; }
      if (k > 1 || (k == 1 && t0 >= 768)) {
        const float4 b = SM_F4(ya + 2 * L_YB - 3120);
        y.x += b.x; y.y += b.y; y.z += b.z; y.w += b.w;
        if (k > 1 || t0 >= 1020) {
          const char* wp = lb + L_W7 + 32 + 2 * (t0 - 1026);
          const uint32_t wl = *(const uint32_t*)wp, wm = *(const uint32_t*)(wp + 4), wh = *(const uint32_t*)(wp + 8);
          y.x = fmaf(kb.x, bf_hi(wl), y.x); y.y = fmaf(kb.x, bf_lo(wm), y.y);
          y.z = fmaf(kb.x, bf_hi(wm), y.z); y.w = fmaf(kb.x, bf_lo(wh), y.w);
          if (k == 3 && n == 127) {
            const uint2 u03 = SM_U2(lb + 528);
            float pre = bf_lo(u03.x);
            y.x = fmaf(kb.y, pre, y.x); pre += bf_hi(u03.x);
            y.y = fmaf(kb.y, pre, y.y); pre += bf_lo(u03.y);
            y.z = fmaf(kb.y, pre, y.z); pre += bf_hi(u03.y);
            y.w = fmaf(kb.y, pre, y.w);
          }
        }
      }
      const uint2 uu = SM_U2(lb + ((t0 >> 8) + 1) * 528 + (t0 & 255) * 2);
      uint2 o;
      o.x = bf2_add(pack_bf16(y.x, y.y), bf2_mul(uu.x, dk));
      o.y = bf2_add(pack_bf16(y.z, y.w), bf2_mul(uu.y, dk));
      *reinterpret_cast<uint2*>(sc.aT + (size_t)(d0 + ch) * L_SEQ + t0) = o;
    }
  }
  __syncwarp();
  if (lane == 0) mbar_arrive(bars + B_COMB);
  if (lead && bid < 128) {
    asm volatile("bar.sync 6, 256;" ::: "memory");
    if (warp < 3 && lane == 0) {
      HFENCE();
      wait_flag(&sc.flags[256 + m], 8);
      mbar_expect_tx(bars + B_X + 8 * (warp + 2), 16384);
      tma2d(sb + (warp + 2) * 16384, tm.xn, (warp + 2) * 64, m * 128, bars + B_X + 8 * (warp + 2));
    }
    __syncwarp();
  }
  CH_SYNC();
  DBG_S(7);
  return pack_params(pnext);
}

__global__ void __cluster_dims__(2, 1, 1) __launch_bounds__(512, 1)
fused_kernel(const __grid_constant__ CUtensorMap tm_x, const __grid_constant__ CUtensorMap tm_w1,
             const __grid_constant__ CUtensorMap tm_w2, const __grid_constant__ CUtensorMap tm_aT,
             const __grid_constant__ CUtensorMap tm_xn, const __grid_constant__ CUtensorMap tm_out,
             const __grid_constant__ CUtensorMap tm_a8,
             const __grid_constant__ Args ar, const __grid_constant__ Scratch sc) {
  extern __shared__ __align__(1024) char smem_raw[];
  DBG_G(28);
  const uint32_t sb = (smem_u32(smem_raw) + 1023) & ~1023u;
  char* sm = smem_raw + (sb - smem_u32(smem_raw));
  const uint32_t bars = sb + OFF_BAR;
  const int tid = threadIdx.x, lane = tid & 31;
  const int warp = __shfl_sync(0xffffffffu, tid >> 5, 0), wg = warp >> 2;
  const int bid = blockIdx.x;
  const int m = bid >> 3, f = bid & 7, rank = f & 1, pr = f >> 1;

  const int dbase = bid < 128 ? bid * 4 : 512 + (bid - 128) * 16;
  uint32_t praw[8];
  load_params(praw, ar, dbase + wg, tid & 127);

  if (lane == 0) {
    if (warp == 8) {
#pragma unroll
      for (int i = 0; i < B_EMPTY / 8; i++) mbar_init(bars + i * 8, 1);
      asm volatile("fence.mbarrier_init.release.cluster;" ::: "memory");
#pragma unroll
      for (int i = 0; i < 4; i++) mbar_expect_tx(bars + B_RB + 8 * i, 16384);
    } else if (warp == 9) {
#pragma unroll
      for (int i = B_EMPTY / 8; i < NBARS; i++) mbar_init(bars + i * 8, 8);
      mbar_init(bars + B_CONV, 16);
      mbar_init(bars + B_COMB, 16);
      asm volatile("fence.mbarrier_init.release.cluster;" ::: "memory");
    } else if (warp == 10) {
      asm volatile("prefetch.tensormap [%0];" ::"l"(&tm_x) : "memory");
    } else if (warp == 11) {
      *reinterpret_cast<Args*>(sm + OFF_ARGS) = ar;
      *reinterpret_cast<Scratch*>(sm + OFF_ARGS + 128) = sc;
    }
  }
  __syncthreads();
  asm volatile("barrier.cluster.arrive.relaxed.aligned;" ::: "memory");

  {
    Maps tm;
    tm.x = &tm_x; tm.w1 = &tm_w1; tm.xn = &tm_xn;
    const int npass = bid < 128 ? 1 : 4;
    if (lane == 0 && (warp & 1) == 0) {
      mbar_expect_tx(bars + B_U, 4096);
      tma2d(sb + xg_off(warp >> 1), &tm_x, dbase & ~7, (warp >> 1) * 256, bars + B_U);
    }
    {
      char* eb = sm + e_off(wg);
      const int n = tid & 127;
      const uint4 z = make_uint4(0, 0, 0, 0);
      SM_U4(eb + E_TAP + n * 16) = z;
      if (n < 104) SM_U4(eb + E_TAP + 2048 + n * 16) = z;
      else if (n == 104) SM_U4(eb + E_W9) = z;
      if (n < 33) SM_U4(sm + l_off(wg) + n * 16) = z;
    }
    uint4 pv = pack_params(praw);
#pragma unroll 1
    for (int pass = 0; pass < npass; pass++)
      pv = ssm_pass(tm, sm, dbase + pass * 4, pass, pv
      );
  }
  __syncthreads();
  if (bid >= 128) {
    if (tid == 0) {
      asm volatile("fence.acq_rel.gpu;" ::: "memory");
      atomicAdd(&sc.flags[304], 1u);
    }
    __syncwarp();
    asm volatile("barrier.cluster.wait.acquire.aligned;" ::: "memory");
    return;
  }

  const uint32_t rdelta = mapa(sb, rank ^ 1) - sb;
  if (wg >= 2) {
    asm volatile("setmaxnreg.dec.sync.aligned.u32 24;");
    asm volatile("barrier.cluster.wait.acquire.aligned;" ::: "memory");
    const int pw = warp - 8;
    if (lane == 0) {
      if (pw < 2) {
        int slot = pw, par = 0;
#pragma unroll 1
        for (int it = 6 + pw; it < 54; it += 2) {
          const int ch = it / 9, s = it - ch * 9;
          const uint32_t fb = bars + B_FULL + 8 * slot;
          mbar_wait(bars + B_EMPTY + 8 * slot, par);
          mbar_expect_tx(fb, STAGE_BYTES);
          tma3d(sb + OFF_ST + slot * STAGE_BYTES, &tm_w1, 0, s * 64, f * 18 + ch * 3, fb);
          slot += 2;
          if (slot >= 6) { slot -= 6; par ^= 1; }
        }
#pragma unroll 1
        for (int pos = 0; pos < 9; pos++) {
          const int chunk = chunk_of(pos, pr, rank);
#pragma unroll 1
          for (slot = pw; slot < 6; slot += 2) {
            const uint32_t fb = bars + B_FULL + 8 * slot;
            mbar_wait(bars + B_EMPTY + 8 * slot, par);
            mbar_expect_tx(fb, STAGE_BYTES);
            tma2d(sb + OFF_ST + slot * STAGE_BYTES, &tm_w2, chunk * 64, f * 576 + slot * 96, fb);
          }
          par ^= 1;
        }
        if (pw == 0) {
          wait_flag(&sc.flags[288 + f * 2], 16);
          mbar_wait(bars + B_EMPTY, par);
          mbar_wait(bars + B_EMPTY + 8, par);
          mbar_expect_tx(bars + B_FULL, 16384);
          tma2d(sb + OFF_ST, &tm_aT, m * 128, f * 64, bars + B_FULL);
          tma2d(sb + OFF_ST + 8192, &tm_aT, m * 128 + 64, f * 64, bars + B_FULL);
          if (atomicAdd(&sc.flags[289 + f * 2], 1u) == 15) { sc.flags[288 + f * 2] = 0; sc.flags[289 + f * 2] = 0; }
        }
      } else if (pw == 2) {
        mbar_wait(bars + B_P1R, 0);
#pragma unroll 1
        for (int k = 0; k < 4; k++) {
          mbar_wait(bars + B_TS + 8 * k, 0);
          HFENCE();
          bulk_s2peer(sb + k * 16384 + rdelta, sb + OFF_STG + k * 16384, 16384, bars + B_RB + 8 * k + rdelta);
        }
#pragma unroll 1
        for (int k = 0; k < 4; k++) mbar_wait(bars + B_RB + 8 * k, 0);
        mbar_arrive_remote(bars + B_FIN + rdelta);
        mbar_wait(bars + B_FIN, 0);
      } else if (pw == 3) {
        mbar_wait(bars + B_TS8, 0);
        HFENCE();
        bulk_s2g_release(sc.slots8 + (size_t)(m * 8 + f) * 4096, sb + OFF_C8, 16384);
#pragma unroll 1
        for (int i = 0; i < 8; i++) atomicAdd(&sc.flags[m * 16 + 8 + i], 1u);
#pragma unroll 1
        for (int k = 0; k < 2; k++) {
          const int chunk = 2 * ((pr + k + 1) & 3) + rank;
          mbar_wait(bars + B_TR + 8 * k, 0);
          HFENCE();
          bulk_s2g_release(sc.slots + (size_t)((m * 8 + chunk) * 3 + k) * 4096, sb + k * 16384, 16384);
          atomicAdd(&sc.flags[320 + (m * 8 + chunk) * 4 + k], 1u);
          DBG_H(16 + k);
          if (k == 0) {
            mbar_expect_tx(bars + B_OWN, 49152);
            wait_flag(&sc.flags[m * 16 + 8 + f], 8);
            sc.flags[m * 16 + 8 + f] = 0;
#pragma unroll 1
            for (int i = 0; i < 8; i++)
              bulk_g2s(sb + OFF_C8 + i * 2048, sc.slots8 + (size_t)(m * 8 + i) * 4096 + f * 512, 2048, bars + B_OWN);
          }
        }
#pragma unroll 1
        for (int j = 0; j < 2; j++) {
          unsigned int* fl = &sc.flags[320 + (m * 8 + f) * 4 + j];
          wait_flag(fl, 1);
          *fl = 0;
          bulk_g2s(sb + j * 16384, sc.slots + (size_t)((m * 8 + f) * 3 + j) * 4096, 16384, bars + B_OWN);
        }
        if (f == 0) sc.flags[256 + m] = 0;
        DBG_H(19);
      } else if (pw == 4) {
        asm volatile("fence.acq_rel.gpu;" ::: "memory");
        atomicAdd(&sc.flags[288 + (bid >> 4) * 2], 1u);
        mbar_wait(bars + B_TR + 8, 0);
        wait_flag(&sc.flags[304], 4);
        mbar_expect_tx(bars + B_A8, 2048);
        tma2d(sb + OFF_A8, &tm_a8, m * 128, 512 + f * 8, bars + B_A8);
        if (atomicAdd(&sc.flags[305], 1u) == 127) { sc.flags[304] = 0; sc.flags[305] = 0; }
      } else {
        HFENCE();
#pragma unroll 1
        for (int kb = pw; kb < 9; kb += 3) {
          mbar_expect_tx(bars + B_X + 8 * kb, kb == 8 ? 16384 + 2304 : 16384);
          tma2d(sb + kb * 16384, &tm_xn, kb * 64, m * 128, bars + B_X + 8 * kb);
          if (kb == 8) {
            bulk_g2s(sb + OFF_B1, ar.b1 + f * 576, 1152, bars + B_X + 64);
            bulk_g2s(sb + OFF_B2, ar.b2, 1152, bars + B_X + 64);
          }
        }
        if (pw == 6) {
          const int chunk = 2 * ((pr + 3) & 3) + rank;
          mbar_wait(bars + B_TR + 16, 0);
          HFENCE();
          bulk_s2g_release(sc.slots + (size_t)((m * 8 + chunk) * 3 + 2) * 4096, sb + 32768, 16384);
          atomicAdd(&sc.flags[320 + (m * 8 + chunk) * 4 + 2], 1u);
          DBG_H(18);
          unsigned int* fl = &sc.flags[320 + (m * 8 + f) * 4 + 2];
          mbar_expect_tx(bars + B_OWN2, 16384);
          wait_flag(fl, 1);
          *fl = 0;
          bulk_g2s(sb + 32768, sc.slots + (size_t)((m * 8 + f) * 3 + 2) * 4096, 16384, bars + B_OWN2);
        }
      }
    }
  } else {
    asm volatile("setmaxnreg.inc.sync.aligned.u32 232;");
    const int wi = warp & 3;
    DBG_T(0);
    MlpCtx c;
    c.bars = bars; c.lane = lane;
    c.dA = (((sb + wg * 8192) & 0x3FFFF) >> 4) | (1u << 16);
    c.dB = ((sb + OFF_ST) & 0x3FFFF) >> 4;

    uint32_t h[144];
    float acc2a[32], acc2b[32];
    {
      float accA[48], accB[48];
#pragma unroll
      for (int i = 0; i < 48; i++) { accA[i] = 0.f; accB[i] = 0.f; }
#pragma unroll
      for (int i = 0; i < 144; i++) h[i] = 0;
      uint32_t baddr = sb + OFF_B1 + (lane & 3) * 4 - 192;
#pragma unroll 1
      for (int j = 0; j < 3; j++) {
        DBG_T(11 + 2 * j);
        p1_chunk<0>(c, j, baddr, accA, accB, h);
        baddr += 192;
        DBG_T(10 + 2 * j);
        p1_chunk<9>(c, j, baddr, accB, accA, h);
        baddr += 192;
      }
      DBG_T(2);
      p2_mma<0>(c, 1, acc2a, h);
      wg_wait<1>();
      stage_release(c, 5);
      fence_regs(accB);
      asm volatile("barrier.cluster.wait.acquire.aligned;" ::: "memory");
      if (lane == 0) { mbar_arrive(bars + B_P1L); mbar_arrive_remote(bars + B_P1R + rdelta); }
      p2_mma<1>(c, 1, acc2a, h);
      gelu_part<0>(baddr, accB); gelu_part<1>(baddr, accB);
      wg_wait<1>(); stage_release(c, 0);
      p2_mma<2>(c, 1, acc2a, h);
      gelu_part<2>(baddr, accB); gelu_part<3>(baddr, accB);
      wg_wait<1>(); stage_release(c, 1);
      p2_mma<3>(c, 1, acc2a, h);
      gelu_part<4>(baddr, accB);
      wg_wait<1>(); stage_release(c, 2);
      p2_mma<4>(c, 1, acc2a, h);
      gelu_part<5>(baddr, accB);
#pragma unroll
      for (int i = 0; i < 24; i++) h[120 + i] = __float_as_uint(accB[(i >> 2) * 8 + (i & 3)]);
      wg_wait<1>(); stage_release(c, 3);
      p2_mma<5>(c, 1, acc2a, h);
      wg_wait<1>(); stage_release(c, 4);
    }
    const uint32_t lbuf = sb + warp * 2048 + lane * 16;
    mbar_wait(bars + B_P1L, 0);
#pragma unroll 1
    for (int pos = 0; pos < 8; pos++) {
      const bool recv = (0x68 >> pos) & 1;
      const int k = recv ? (pos - 2) >> 1 : (pos + 1) >> 1;
      const int ks = k > 3 ? 3 : k;
      const uint32_t addr = lbuf + ks * 16384 + (recv ? 0 : OFF_STG);
      const uint32_t sig = bars + (recv ? B_TR + 8 * k : pos == 1 ? B_TS8 : B_TS + 8 * ks);
      wg_wait<0>();
      fence_regs(acc2a);
      uint32_t pk[16];
#pragma unroll
      for (int i = 0; i < 16; i++) pk[i] = pack_bf16(acc2a[2 * i], acc2a[2 * i + 1]);
      const uint32_t par = pos & 1;
      p2_mma<0>(c, par, acc2a, h);
      stage_release(c, 5);
      p2_mma<1>(c, par, acc2a, h);
      DBG_T(20 + pos);
      if (recv) {
        mbar_wait(bars + B_RB + k * 8, 0);
#pragma unroll
        for (int i = 0; i < 4; i++) {
          const float4 r = lds128f(addr + i * 512);
          pk[4 * i] = bf2_add(pk[4 * i], __float_as_uint(r.x)); pk[4 * i + 1] = bf2_add(pk[4 * i + 1], __float_as_uint(r.y));
          pk[4 * i + 2] = bf2_add(pk[4 * i + 2], __float_as_uint(r.z)); pk[4 * i + 3] = bf2_add(pk[4 * i + 3], __float_as_uint(r.w));
        }
      }
      if (pos == 1) {
        const uint32_t a8 = sb + OFF_C8 + warp * 256 + lane * 8;
#pragma unroll
        for (int q = 0; q < 8; q++)
          asm volatile("st.shared.v2.u32 [%0], {%1,%2};" ::"r"(a8 + q * 2048), "r"(pk[2 * q]), "r"(pk[2 * q + 1]) : "memory");
      } else {
#pragma unroll
        for (int i = 0; i < 4; i++) sts128(addr + i * 512, pk[4 * i], pk[4 * i + 1], pk[4 * i + 2], pk[4 * i + 3]);
      }
      __syncwarp();
      if (lane == 0) mbar_arrive(sig);
      wg_wait<1>(); stage_release(c, 0);
      p2_mma<2>(c, par, acc2a, h);
      wg_wait<1>(); stage_release(c, 1);
      p2_mma<3>(c, par, acc2a, h);
      wg_wait<1>(); stage_release(c, 2);
      p2_mma<4>(c, par, acc2a, h);
      wg_wait<1>(); stage_release(c, 3);
      p2_mma<5>(c, par, acc2a, h);
      wg_wait<1>(); stage_release(c, 4);
    }
    DBG_T(3);
    {
      const int g = lane >> 2, cc = lane & 3;
      const int t0 = m * 128 + warp * 16 + g;
      const uint2 ga = __ldcg(&sc.gate[t0]), gb = __ldcg(&sc.gate[t0 + 8]);
#pragma unroll
      for (int i = 0; i < 32; i++) acc2b[i] = 0.f;
      auto add_tile = [&](int k) {
#pragma unroll
        for (int i = 0; i < 4; i++) {
          float4 r = lds128f(lbuf + k * 16384 + i * 512);
          const uint32_t w0 = __float_as_uint(r.x), w1 = __float_as_uint(r.y), w2 = __float_as_uint(r.z), w3 = __float_as_uint(r.w);
          acc2b[8 * i + 0] += bf_lo(w0); acc2b[8 * i + 1] += bf_hi(w0); acc2b[8 * i + 2] += bf_lo(w1); acc2b[8 * i + 3] += bf_hi(w1);
          acc2b[8 * i + 4] += bf_lo(w2); acc2b[8 * i + 5] += bf_hi(w2); acc2b[8 * i + 6] += bf_lo(w3); acc2b[8 * i + 7] += bf_hi(w3);
        }
      };
      mbar_wait(bars + B_OWN, 0);
      add_tile(0);
      add_tile(1);
      float c8[4] = {0.f, 0.f, 0.f, 0.f};
#pragma unroll
      for (int i = 0; i < 8; i++) {
        uint32_t w0, w1;
        asm volatile("ld.shared.v2.u32 {%0,%1}, [%2];" : "=r"(w0), "=r"(w1) : "r"(sb + OFF_C8 + i * 2048 + warp * 256 + lane * 8));
        c8[0] += bf_lo(w0); c8[1] += bf_hi(w0); c8[2] += bf_lo(w1); c8[3] += bf_hi(w1);
      }
      mbar_wait(bars + B_RB + 24, 0);
      add_tile(3);
      mbar_wait(bars + B_OWN2, 0);
      DBG_T(8);
      add_tile(2);
      DBG_T(9);
      mbar_wait(bars + B_FULL, 0);
      wg_wait<0>();
      fence_regs(acc2a);
      DBG_T(4);
#pragma unroll
      for (int jj = 0; jj < 4; jj++) {
        uint32_t a[4];
        {
          const int dl = 8 * (2 * jj + (lane >> 4)) + (lane & 7);
          const int chk = 2 * wi + ((lane >> 3) & 1);
          ldsm4t(a, sb + OFF_ST + wg * 8192 + dl * 128 + ((chk ^ (dl & 7)) << 4));
        }
        uint32_t o[4];
#pragma unroll
        for (int e = 0; e < 2; e++) {
          const int q = 2 * jj + e;
          uint32_t bb = lds32(sb + OFF_B2 + (f * 64 + q * 8 + cc * 2) * 2);
          uint32_t v0 = bf2_add(pack_bf16(acc2a[4 * q] + acc2b[4 * q], acc2a[4 * q + 1] + acc2b[4 * q + 1]), bb);
          uint32_t v1 = bf2_add(pack_bf16(acc2a[4 * q + 2] + acc2b[4 * q + 2], acc2a[4 * q + 3] + acc2b[4 * q + 3]), bb);
          o[2 * e] = bf2_add(bf2_mul(ga.x, a[2 * e]), bf2_mul(ga.y, v0));
          o[2 * e + 1] = bf2_add(bf2_mul(gb.x, a[2 * e + 1]), bf2_mul(gb.y, v1));
        }
        {
          const int row = (lane & 7) + ((lane >> 3) & 1) * 8;
          const uint32_t addr = sb + 49152 + warp * 2048 + row * 128 + (((2 * jj + (lane >> 4)) ^ (row & 7)) << 4);
          asm volatile("stmatrix.sync.aligned.m8n8.x4.shared.b16 [%0], {%1,%2,%3,%4};"
                       ::"r"(addr), "r"(o[0]), "r"(o[1]), "r"(o[2]), "r"(o[3]) : "memory");
        }
      }
      asm volatile("fence.proxy.async.shared::cta;" ::: "memory");
      __syncwarp();
      if (lane == 0) {
        asm volatile("cp.async.bulk.tensor.2d.global.shared::cta.bulk_group [%0, {%2, %3}], [%1];\n"
                     "cp.async.bulk.commit_group;"
                     ::"l"(&tm_out), "r"(sb + 49152 + warp * 2048), "r"(f * 64), "r"(m * 128 + warp * 16) : "memory");
      }
      __syncwarp();
      mbar_wait(bars + B_A8, 0);
      {
        __nv_bfloat16* op = ar.out + (size_t)t0 * D_MOD + cc * 2 + 512 + f * 8;
        uint32_t a0, a1;
        const uint32_t addr = sb + OFF_A8 + (lane & 7) * 256 + (warp * 2 + ((lane >> 3) & 1)) * 16;
        asm volatile("ldmatrix.sync.aligned.m8n8.x2.trans.shared.b16 {%0,%1}, [%2];" : "=r"(a0), "=r"(a1) : "r"(addr));
        const uint32_t bb = lds32(sb + OFF_B2 + (512 + f * 8 + cc * 2) * 2);
        const uint32_t v0 = bf2_add(pack_bf16(c8[0], c8[1]), bb), v1 = bf2_add(pack_bf16(c8[2], c8[3]), bb);
        *reinterpret_cast<uint32_t*>(op) = bf2_add(bf2_mul(ga.x, a0), bf2_mul(ga.y, v0));
        *reinterpret_cast<uint32_t*>(op + 8 * D_MOD) = bf2_add(bf2_mul(gb.x, a1), bf2_mul(gb.y, v1));
      }
      if (lane == 0) asm volatile("cp.async.bulk.wait_group.read 0;" ::: "memory");
      DBG_T(5);
      DBG_G(29);
    }
  }
}

typedef CUresult (*EncodeTiledFn)(CUtensorMap*, CUtensorMapDataType, cuuint32_t, void*, const cuuint64_t*,
                                  const cuuint64_t*, const cuuint32_t*, const cuuint32_t*, CUtensorMapInterleave,
                                  CUtensorMapSwizzle, CUtensorMapL2promotion, CUtensorMapFloatOOBfill);

static void make_map(EncodeTiledFn enc, CUtensorMap* tm, const void* base, uint64_t inner, uint64_t outer, uint32_t binner,
                     uint32_t bouter, CUtensorMapSwizzle swz) {
  cuuint64_t gd[2] = {inner, outer};
  cuuint64_t gs[1] = {inner * 2};
  cuuint32_t bd[2] = {binner, bouter};
  cuuint32_t es[2] = {1, 1};
  enc(tm, CU_TENSOR_MAP_DATA_TYPE_BFLOAT16, 2, const_cast<void*>(base), gd, gs, bd, es, CU_TENSOR_MAP_INTERLEAVE_NONE, swz,
      CU_TENSOR_MAP_L2_PROMOTION_L2_128B, CU_TENSOR_MAP_FLOAT_OOB_FILL_NONE);
}

extern "C" void kernel_launch(void* const* d_in, const int* in_sizes, int n_in, void* d_out, int out_size) {
  typedef const __nv_bfloat16* BP;
  Args ar;
  ar.u = (BP)d_in[0]; ar.Are = (BP)d_in[1]; ar.Aim = (BP)d_in[2]; ar.Bre = (BP)d_in[3]; ar.Bim = (BP)d_in[4];
  ar.Cre = (BP)d_in[5]; ar.Cim = (BP)d_in[6]; ar.logdt = (BP)d_in[7]; ar.Dskip = (BP)d_in[8];
  ar.w1 = (BP)d_in[10]; ar.b1 = (BP)d_in[11]; ar.w2 = (BP)d_in[12]; ar.b2 = (BP)d_in[13]; ar.gate_w = (BP)d_in[14];
  ar.out = (__nv_bfloat16*)d_out;

  static EncodeTiledFn enc = nullptr;
  static Scratch sc;
  if (!enc) {
    cudaDriverEntryPointQueryResult qr;
    cudaGetDriverEntryPoint("cuTensorMapEncodeTiled", (void**)&enc, cudaEnableDefault, &qr);
    cudaGetSymbolAddress((void**)&sc.aT, g_aT);
    cudaGetSymbolAddress((void**)&sc.xn, g_xn);
    cudaGetSymbolAddress((void**)&sc.gate, g_gate);
    cudaGetSymbolAddress((void**)&sc.slots, g_slots);
    cudaGetSymbolAddress((void**)&sc.slots8, g_slots8);
    cudaGetSymbolAddress((void**)&sc.flags, g_flags);
    sc.dbg = nullptr;
    cudaFuncSetAttribute(fused_kernel, cudaFuncAttributeMaxDynamicSharedMemorySize, SMEM_BYTES);
  }
  CUtensorMap tm_x, tm_w1, tm_w2, tm_aT, tm_xn, tm_out, tm_a8;
  make_map(enc, &tm_a8, sc.aT, L_SEQ, D_MOD, 128, 8, CU_TENSOR_MAP_SWIZZLE_NONE);
  make_map(enc, &tm_x, ar.u, D_MOD, L_SEQ, 8, 256, CU_TENSOR_MAP_SWIZZLE_NONE);
  make_map(enc, &tm_w2, ar.w2, D_MOD, F_HID, 64, 96, CU_TENSOR_MAP_SWIZZLE_128B);
  make_map(enc, &tm_aT, sc.aT, L_SEQ, D_MOD, 64, 64, CU_TENSOR_MAP_SWIZZLE_128B);
  make_map(enc, &tm_xn, sc.xn, D_MOD, L_SEQ, 64, 128, CU_TENSOR_MAP_SWIZZLE_128B);
  make_map(enc, &tm_out, d_out, D_MOD, L_SEQ, 64, 16, CU_TENSOR_MAP_SWIZZLE_128B);
  {
    cuuint64_t gd[3] = {32, D_MOD, F_HID / 32};
    cuuint64_t gs[2] = {F_HID * 2, 64};
    cuuint32_t bd[3] = {32, 64, 3};
    cuuint32_t es[3] = {1, 1, 1};
    enc(&tm_w1, CU_TENSOR_MAP_DATA_TYPE_BFLOAT16, 3, (void*)ar.w1, gd, gs, bd, es, CU_TENSOR_MAP_INTERLEAVE_NONE,
        CU_TENSOR_MAP_SWIZZLE_64B, CU_TENSOR_MAP_L2_PROMOTION_L2_128B, CU_TENSOR_MAP_FLOAT_OOB_FILL_NONE);
  }
  fused_kernel<<<132, 512, SMEM_BYTES, cudaStreamPerThread>>>(tm_x, tm_w1, tm_w2, tm_aT, tm_xn, tm_out, tm_a8, ar, sc);
}
```
